```python
import torch

def _softmax(x, axis=-1):
    return torch.softmax(x, dim=axis)
def _gelu(x):
    return torch.nn.functional.gelu(x, approximate="tanh")
def _silu(x):
    return torch.nn.functional.silu(x)
def _sigmoid(x):
    return torch.sigmoid(x)
def _layernorm(x, axis=-1, eps=1e-5):
    m = x.mean(dim=axis, keepdim=True)
    v = x.var(dim=axis, keepdim=True, unbiased=False)
    return (x - m) / torch.sqrt(v + eps)
def _scatter_add(tgt, idx, src, axis=0):
    return tgt.clone().index_add_(axis, idx, src)
def _segment_sum(src, seg, n):
    out = torch.zeros((n,) + src.shape[1:], dtype=src.dtype)
    return out.index_add_(0, seg, src)
def _pad(x, pw):
    flat = tuple(v for pair in reversed(pw) for v in pair)
    return torch.nn.functional.pad(x, flat)

kernel_name = 'concat_heads__ssm_conv_s4__ssm_conv_h3__prompt'

def setup_inputs():

    _w = (lambda a: (lambda t: t.to(torch.bfloat16) if t.is_floating_point() else t)(torch.as_tensor(a)))
    def _A_setup():
        B, L, D, N = 1, 2048, 576, 128
        A_re = -(lambda _x: torch.exp(torch.as_tensor(_x)))((lambda *s: torch.randn(*s, dtype=torch.bfloat16) * 6.4)(D, N))
        A_im = torch.pi * (lambda *s: torch.randn(*s, dtype=torch.bfloat16) * 0.05)(D, N)
        B_re = (lambda *s: torch.randn(*s, dtype=torch.bfloat16) * 0.1)(D, N)
        B_im = (lambda *s: torch.randn(*s, dtype=torch.bfloat16) * 0.1)(D, N)
        C_re = (lambda *s: torch.randn(*s, dtype=torch.bfloat16) * 0.1)(D, N)
        C_im = (lambda *s: torch.randn(*s, dtype=torch.bfloat16) * 0.1)(D, N)
        log_dt = (lambda *s: torch.randn(*s, dtype=torch.bfloat16) * 0.05)(D) * 0.5 - 4.0
        Dskip = (lambda *s: torch.randn(*s, dtype=torch.bfloat16) * 0.05)(D)
        return {
            "u": _w((lambda *s: torch.randn(*s, dtype=torch.bfloat16) * 0.05)(B, L, D)),
            "A_re": _w(A_re),
            "A_im": _w(A_im),
            "B_re": _w(B_re),
            "B_im": _w(B_im),
            "C_re": _w(C_re),
            "C_im": _w(C_im),
            "log_dt": _w(log_dt),
            "Dskip": _w(Dskip),
        }
    _A_in = _A_setup()

    def _B_setup():
        B, S, D = 1, 2048, 576
        ks = 4
        return {
            "q": _w((lambda *s: torch.randn(*s, dtype=torch.bfloat16) * 0.05)(B, S, D)),
            "k": _w((lambda *s: torch.randn(*s, dtype=torch.bfloat16) * 0.4)(B, S, D)),
            "v": _w((lambda *s: torch.randn(*s, dtype=torch.bfloat16) * 0.4)(B, S, D)),
            "shift_k": _w((lambda *s: torch.randn(*s, dtype=torch.bfloat16) * 0.4)(D, ks) * 0.5),
            "ssm_k": _w((lambda *s: torch.randn(*s, dtype=torch.bfloat16) * 0.4)(D, S) * (1.0 / S ** 0.5)),
            "ssm_D": _w((lambda *s: torch.randn(*s, dtype=torch.bfloat16) * 0.4)(D)),
        }
    _B_in = _B_setup()

    return {
        "A_u": _A_in["u"],
        "A_A_re": _A_in["A_re"],
        "A_A_im": _A_in["A_im"],
        "A_B_re": _A_in["B_re"],
        "A_B_im": _A_in["B_im"],
        "A_C_re": _A_in["C_re"],
        "A_C_im": _A_in["C_im"],
        "A_log_dt": _A_in["log_dt"],
        "A_Dskip": _A_in["Dskip"],
        "B_q": _B_in["q"],
        "B_k": _B_in["k"],
        "B_v": _B_in["v"],
        "B_shift_k": _B_in["shift_k"],
        "B_ssm_k": _B_in["ssm_k"],
        "B_ssm_D": _B_in["ssm_D"],
    }

def reference(A_u, A_A_re, A_A_im, A_B_re, A_B_im, A_C_re, A_C_im, A_log_dt, A_Dskip, B_q, B_k, B_v, B_shift_k, B_ssm_k, B_ssm_D):
    def _A_ref(u, A_re, A_im, B_re, B_im, C_re, C_im, log_dt, Dskip):
        Bsz, L, D = u.shape
        dt = torch.exp(log_dt)[:, None]
        A = A_re + 1j * A_im
        Bc = B_re + 1j * B_im
        Cc = C_re + 1j * C_im
        logdA = dt * A
        dB = dt * Bc
        l = (lambda x, dt: x.to(dt))(torch.arange(L), A_re.dtype)
        P = torch.exp(logdA[:, :, None] * l[None, None, :])
        K = torch.einsum("dn,dnl,dn->dl", Cc, P, dB).real
        L2 = 2 * L
        Kp = _pad(K, ((0, 0), (0, L)))
        up = (lambda x, *d: x.permute(*d))(u, 0, 2, 1)
        up = _pad(up, ((0, 0), (0, 0), (0, L)))
        Kf = (lambda x, axes=(-2,-1): torch.fft.rfft2(x.float(), dim=axes))(Kp[:, None, :], axes=(-2, -1))
        Uf = (lambda x, axes=(-2,-1): torch.fft.rfft2(x.float(), dim=axes))(up[:, :, None, :], axes=(-2, -1))
        Yf = Uf * Kf[None, :, :, :]
        y = (lambda x, s, axes=(-2,-1): torch.fft.irfft2(x, s=s, dim=axes).to(torch.bfloat16))(Yf, (1, L2), axes=(-2, -1))[:, :, 0, :L]
        y = (lambda x, *d: x.permute(*d))(y, 0, 2, 1) + u * Dskip[None, None, :]
        return y

    def _B_ref(q, k, v, shift_k, ssm_k, ssm_D):
        B, S, D = q.shape
        ks = shift_k.shape[-1]
        k_pad = _pad(k, ((0, 0), (ks - 1, 0), (0, 0)))
        k_shift = torch.zeros_like(k)
        for t in range(ks):
            k_shift = k_shift + k_pad[:, t:t + S, :] * shift_k[:, ks - 1 - t][None, None, :]
        kv = k_shift * v
        L = 2 * S
        kv_pad = _pad(kv, ((0, 0), (0, S), (0, 0)))
        kf_pad = _pad(ssm_k, ((0, 0), (0, S)))
        kv_f = (lambda x, axes=(-2,-1): torch.fft.rfft2(x.float(), dim=axes))(kv_pad[:, None, :, :], axes=(1, 2))
        kf_f = (lambda x, axes=(-2,-1): torch.fft.rfft2(x.float(), dim=axes))(kf_pad[:, None, :], axes=(1, 2))
        kf_f = (lambda x, *d: x.permute(*d))(kf_f, 1, 2, 0)
        y_f = kv_f * kf_f[None, :, :, :]
        y = (lambda x, s, axes=(-2,-1): torch.fft.irfft2(x, s=s, dim=axes).to(torch.bfloat16))(y_f, (1, L), axes=(1, 2))[:, 0, :S, :]
        y = y + kv * ssm_D[None, None, :]
        return q * y

    a = _A_ref(A_u, A_A_re, A_A_im, A_B_re, A_B_im, A_C_re, A_C_im, A_log_dt, A_Dskip)
    b = _B_ref(B_q, B_k, B_v, B_shift_k, B_ssm_k, B_ssm_D)
    return torch.concatenate([a, b], axis=-1)
```

```cpp
#include <cuda_runtime.h>
#include <cuda_bf16.h>
#include <cuda.h>
#include <stdint.h>

#define G1 3
#define UG 1
#define STAGGER 400
#define PDELAY 800
namespace s4h3 {

constexpr int SEQ = 2048, DCH = 576, NMODE = 128;
constexpr int NTHREADS = 512;

constexpr uint32_t OFF_KB  = 0;
constexpr uint32_t OFF_XT  = 49152;
constexpr uint32_t OFF_RU  = 98304;
constexpr uint32_t OFF_RK1 = 122880;
constexpr uint32_t OFF_RV1 = 135936;
constexpr uint32_t OFF_RK2 = 148224;
constexpr uint32_t OFF_RV2 = 161280;
constexpr uint32_t OFF_RQ  = 173568;
constexpr uint32_t OFF_YA  = 198144;
constexpr uint32_t OFF_F2  = 222720;
constexpr uint32_t OFF_BAR = 230912;
constexpr uint32_t OFF_D = OFF_BAR + 448;
constexpr uint32_t SMEM_BYTES = 231936;
constexpr int B_U = 0, B_KV = 6, B_Q = 12, B_S = 18, B_F = 21, B_KG = 22, B_KR = 23, B_X = 24, B_Y = 36, B_P1 = 48, B_NUM = 49;

__device__ const __align__(128) uint32_t F2TAB[2048] = {
0x3f803f80,0x3f803f80,0x3f803f80,0x3f803f80,0x3f6d3f80,0x3ec43f35,0xbec40000,0xbf6dbf35,
0x3f353f80,0xbf350000,0xbf35bf80,0x3f350000,0x3ec43f80,0xbf6dbf35,0x3f6d0000,0xbec43f35,
0x00003f80,0x0000bf80,0x00003f80,0x0000bf80,0xbec43f80,0x3f6dbf35,0xbf6d0000,0x3ec43f35,
0xbf353f80,0x3f350000,0x3f35bf80,0xbf350000,0xbf6d3f80,0xbec43f35,0x3ec40000,0x3f6dbf35,
0x3f803f80,0x3f803f80,0x3f803f80,0x3f803f80,0xbf6dbf80,0xbec4bf35,0x3ec40000,0x3f6d3f35,
0x3f353f80,0xbf350000,0xbf35bf80,0x3f350000,0xbec4bf80,0x3f6d3f35,0xbf6d0000,0x3ec4bf35,
0x00003f80,0x0000bf80,0x00003f80,0x0000bf80,0x3ec4bf80,0xbf6d3f35,0x3f6d0000,0xbec4bf35,
0xbf353f80,0x3f350000,0x3f35bf80,0xbf350000,0x3f6dbf80,0x3ec4bf35,0xbec40000,0xbf6d3f35,
0xbf803f80,0xbf803f80,0xbf803f80,0xbf803f80,0xbf6d3f80,0xbec43f35,0x3ec40000,0x3f6dbf35,
0xbf353f80,0x3f350000,0x3f35bf80,0xbf350000,0xbec43f80,0x3f6dbf35,0xbf6d0000,0x3ec43f35,
0x00003f80,0x0000bf80,0x00003f80,0x0000bf80,0x3ec43f80,0xbf6dbf35,0x3f6d0000,0xbec43f35,
0x3f353f80,0xbf350000,0xbf35bf80,0x3f350000,0x3f6d3f80,0x3ec43f35,0xbec40000,0xbf6dbf35,
0xbf803f80,0xbf803f80,0xbf803f80,0xbf803f80,0x3f6dbf80,0x3ec4bf35,0xbec40000,0xbf6d3f35,
0xbf353f80,0x3f350000,0x3f35bf80,0xbf350000,0x3ec4bf80,0xbf6d3f35,0x3f6d0000,0xbec4bf35,
0x00003f80,0x0000bf80,0x00003f80,0x0000bf80,0xbec4bf80,0x3f6d3f35,0xbf6d0000,0x3ec4bf35,
0x3f353f80,0xbf350000,0xbf35bf80,0x3f350000,0xbf6dbf80,0xbec4bf35,0x3ec40000,0x3f6d3f35,
0x00000000,0x00000000,0x00000000,0x00000000,0x3ec40000,0x3f6d3f35,0x3f6d3f80,0x3ec43f35,
0x3f350000,0x3f353f80,0xbf350000,0xbf35bf80,0x3f6d0000,0xbec43f35,0xbec4bf80,0x3f6d3f35,
0x3f800000,0xbf800000,0x3f800000,0xbf800000,0x3f6d0000,0xbec4bf35,0xbec43f80,0x3f6dbf35,
0x3f350000,0x3f35bf80,0xbf350000,0xbf353f80,0x3ec40000,0x3f6dbf35,0x3f6dbf80,0x3ec4bf35,
0x00000000,0x00000000,0x00000000,0x00000000,0xbec40000,0xbf6dbf35,0xbf6dbf80,0xbec4bf35,
0x3f350000,0x3f353f80,0xbf350000,0xbf35bf80,0xbf6d0000,0x3ec4bf35,0x3ec43f80,0xbf6dbf35,
0x3f800000,0xbf800000,0x3f800000,0xbf800000,0xbf6d0000,0x3ec43f35,0x3ec4bf80,0xbf6d3f35,
0x3f350000,0x3f35bf80,0xbf350000,0xbf353f80,0xbec40000,0xbf6d3f35,0xbf6d3f80,0xbec43f35,
0x00000000,0x00000000,0x00000000,0x00000000,0xbec40000,0xbf6d3f35,0xbf6d3f80,0xbec43f35,
0xbf350000,0xbf353f80,0x3f350000,0x3f35bf80,0xbf6d0000,0x3ec43f35,0x3ec4bf80,0xbf6d3f35,
0xbf800000,0x3f800000,0xbf800000,0x3f800000,0xbf6d0000,0x3ec4bf35,0x3ec43f80,0xbf6dbf35,
0xbf350000,0xbf35bf80,0x3f350000,0x3f353f80,0xbec40000,0xbf6dbf35,0xbf6dbf80,0xbec4bf35,
0x00000000,0x00000000,0x00000000,0x00000000,0x3ec40000,0x3f6dbf35,0x3f6dbf80,0x3ec4bf35,
0xbf350000,0xbf353f80,0x3f350000,0x3f35bf80,0x3f6d0000,0xbec4bf35,0xbec43f80,0x3f6dbf35,
0xbf800000,0x3f800000,0xbf800000,0x3f800000,0x3f6d0000,0xbec43f35,0xbec4bf80,0x3f6d3f35,
0xbf350000,0xbf35bf80,0x3f350000,0x3f353f80,0x3ec40000,0x3f6d3f35,0x3f6d3f80,0x3ec43f35,
0x00000000,0x00000000,0x00000000,0x00000000,0xbec40000,0xbf6dbf35,0xbf6dbf80,0xbec4bf35,
0xbf350000,0xbf35bf80,0x3f350000,0x3f353f80,0xbf6d0000,0x3ec4bf35,0x3ec43f80,0xbf6dbf35,
0xbf800000,0x3f800000,0xbf800000,0x3f800000,0xbf6d0000,0x3ec43f35,0x3ec4bf80,0xbf6d3f35,
0xbf350000,0xbf353f80,0x3f350000,0x3f35bf80,0xbec40000,0xbf6d3f35,0xbf6d3f80,0xbec43f35,
0x00000000,0x00000000,0x00000000,0x00000000,0x3ec40000,0x3f6d3f35,0x3f6d3f80,0x3ec43f35,
0xbf350000,0xbf35bf80,0x3f350000,0x3f353f80,0x3f6d0000,0xbec43f35,0xbec4bf80,0x3f6d3f35,
0xbf800000,0x3f800000,0xbf800000,0x3f800000,0x3f6d0000,0xbec4bf35,0xbec43f80,0x3f6dbf35,
0xbf350000,0xbf353f80,0x3f350000,0x3f35bf80,0x3ec40000,0x3f6dbf35,0x3f6dbf80,0x3ec4bf35,
0x00000000,0x00000000,0x00000000,0x00000000,0x3ec40000,0x3f6dbf35,0x3f6dbf80,0x3ec4bf35,
0x3f350000,0x3f35bf80,0xbf350000,0xbf353f80,0x3f6d0000,0xbec4bf35,0xbec43f80,0x3f6dbf35,
0x3f800000,0xbf800000,0x3f800000,0xbf800000,0x3f6d0000,0xbec43f35,0xbec4bf80,0x3f6d3f35,
0x3f350000,0x3f353f80,0xbf350000,0xbf35bf80,0x3ec40000,0x3f6d3f35,0x3f6d3f80,0x3ec43f35,
0x00000000,0x00000000,0x00000000,0x00000000,0xbec40000,0xbf6d3f35,0xbf6d3f80,0xbec43f35,
0x3f350000,0x3f35bf80,0xbf350000,0xbf353f80,0xbf6d0000,0x3ec43f35,0x3ec4bf80,0xbf6d3f35,
0x3f800000,0xbf800000,0x3f800000,0xbf800000,0xbf6d0000,0x3ec4bf35,0x3ec43f80,0xbf6dbf35,
0x3f350000,0x3f353f80,0xbf350000,0xbf35bf80,0xbec40000,0xbf6dbf35,0xbf6dbf80,0xbec4bf35,
0x3f803f80,0x3f803f80,0x3f803f80,0x3f803f80,0x3f6d3f80,0x3ec43f35,0xbec40000,0xbf6dbf35,
0x3f353f80,0xbf350000,0xbf35bf80,0x3f350000,0x3ec43f80,0xbf6dbf35,0x3f6d0000,0xbec43f35,
0x00003f80,0x0000bf80,0x00003f80,0x0000bf80,0xbec43f80,0x3f6dbf35,0xbf6d0000,0x3ec43f35,
0xbf353f80,0x3f350000,0x3f35bf80,0xbf350000,0xbf6d3f80,0xbec43f35,0x3ec40000,0x3f6dbf35,
0x3f803f80,0x3f803f80,0x3f803f80,0x3f803f80,0xbf6dbf80,0xbec4bf35,0x3ec40000,0x3f6d3f35,
0x3f353f80,0xbf350000,0xbf35bf80,0x3f350000,0xbec4bf80,0x3f6d3f35,0xbf6d0000,0x3ec4bf35,
0x00003f80,0x0000bf80,0x00003f80,0x0000bf80,0x3ec4bf80,0xbf6d3f35,0x3f6d0000,0xbec4bf35,
0xbf353f80,0x3f350000,0x3f35bf80,0xbf350000,0x3f6dbf80,0x3ec4bf35,0xbec40000,0xbf6d3f35,
0xbf803f80,0xbf803f80,0xbf803f80,0xbf803f80,0xbf6d3f80,0xbec43f35,0x3ec40000,0x3f6dbf35,
0xbf353f80,0x3f350000,0x3f35bf80,0xbf350000,0xbec43f80,0x3f6dbf35,0xbf6d0000,0x3ec43f35,
0x00003f80,0x0000bf80,0x00003f80,0x0000bf80,0x3ec43f80,0xbf6dbf35,0x3f6d0000,0xbec43f35,
0x3f353f80,0xbf350000,0xbf35bf80,0x3f350000,0x3f6d3f80,0x3ec43f35,0xbec40000,0xbf6dbf35,
0xbf803f80,0xbf803f80,0xbf803f80,0xbf803f80,0x3f6dbf80,0x3ec4bf35,0xbec40000,0xbf6d3f35,
0xbf353f80,0x3f350000,0x3f35bf80,0xbf350000,0x3ec4bf80,0xbf6d3f35,0x3f6d0000,0xbec4bf35,
0x00003f80,0x0000bf80,0x00003f80,0x0000bf80,0xbec4bf80,0x3f6d3f35,0xbf6d0000,0x3ec4bf35,
0x3f353f80,0xbf350000,0xbf35bf80,0x3f350000,0xbf6dbf80,0xbec4bf35,0x3ec40000,0x3f6d3f35,
0x3f803f80,0x3f803f80,0x3f803f80,0x3f803f80,0x3f6d3f80,0x3ec43f35,0xbec40000,0xbf6dbf35,
0x3f353f80,0xbf350000,0xbf35bf80,0x3f350000,0x3ec43f80,0xbf6dbf35,0x3f6d0000,0xbec43f35,
0x00003f80,0x0000bf80,0x00003f80,0x0000bf80,0xbec43f80,0x3f6dbf35,0xbf6d0000,0x3ec43f35,
0xbf353f80,0x3f350000,0x3f35bf80,0xbf350000,0xbf6d3f80,0xbec43f35,0x3ec40000,0x3f6dbf35,
0x3f803f80,0x3f803f80,0x3f803f80,0x3f803f80,0xbf6dbf80,0xbec4bf35,0x3ec40000,0x3f6d3f35,
0x3f353f80,0xbf350000,0xbf35bf80,0x3f350000,0xbec4bf80,0x3f6d3f35,0xbf6d0000,0x3ec4bf35,
0x00003f80,0x0000bf80,0x00003f80,0x0000bf80,0x3ec4bf80,0xbf6d3f35,0x3f6d0000,0xbec4bf35,
0xbf353f80,0x3f350000,0x3f35bf80,0xbf350000,0x3f6dbf80,0x3ec4bf35,0xbec40000,0xbf6d3f35,
0xbf803f80,0xbf803f80,0xbf803f80,0xbf803f80,0xbf6d3f80,0xbec43f35,0x3ec40000,0x3f6dbf35,
0xbf353f80,0x3f350000,0x3f35bf80,0xbf350000,0xbec43f80,0x3f6dbf35,0xbf6d0000,0x3ec43f35,
0x00003f80,0x0000bf80,0x00003f80,0x0000bf80,0x3ec43f80,0xbf6dbf35,0x3f6d0000,0xbec43f35,
0x3f353f80,0xbf350000,0xbf35bf80,0x3f350000,0x3f6d3f80,0x3ec43f35,0xbec40000,0xbf6dbf35,
0xbf803f80,0xbf803f80,0xbf803f80,0xbf803f80,0x3f6dbf80,0x3ec4bf35,0xbec40000,0xbf6d3f35,
0xbf353f80,0x3f350000,0x3f35bf80,0xbf350000,0x3ec4bf80,0xbf6d3f35,0x3f6d0000,0xbec4bf35,
0x00003f80,0x0000bf80,0x00003f80,0x0000bf80,0xbec4bf80,0x3f6d3f35,0xbf6d0000,0x3ec4bf35,
0x3f353f80,0xbf350000,0xbf35bf80,0x3f350000,0xbf6dbf80,0xbec4bf35,0x3ec40000,0x3f6d3f35,
0x00000000,0x00000000,0x00000000,0x00000000,0xbec40000,0xbf6dbf35,0xbf6dbf80,0xbec4bf35,
0xbf350000,0xbf35bf80,0x3f350000,0x3f353f80,0xbf6d0000,0x3ec4bf35,0x3ec43f80,0xbf6dbf35,
0xbf800000,0x3f800000,0xbf800000,0x3f800000,0xbf6d0000,0x3ec43f35,0x3ec4bf80,0xbf6d3f35,
0xbf350000,0xbf353f80,0x3f350000,0x3f35bf80,0xbec40000,0xbf6d3f35,0xbf6d3f80,0xbec43f35,
0x00000000,0x00000000,0x00000000,0x00000000,0x3ec40000,0x3f6d3f35,0x3f6d3f80,0x3ec43f35,
0xbf350000,0xbf35bf80,0x3f350000,0x3f353f80,0x3f6d0000,0xbec43f35,0xbec4bf80,0x3f6d3f35,
0xbf800000,0x3f800000,0xbf800000,0x3f800000,0x3f6d0000,0xbec4bf35,0xbec43f80,0x3f6dbf35,
0xbf350000,0xbf353f80,0x3f350000,0x3f35bf80,0x3ec40000,0x3f6dbf35,0x3f6dbf80,0x3ec4bf35,
0x00000000,0x00000000,0x00000000,0x00000000,0x3ec40000,0x3f6dbf35,0x3f6dbf80,0x3ec4bf35,
0x3f350000,0x3f35bf80,0xbf350000,0xbf353f80,0x3f6d0000,0xbec4bf35,0xbec43f80,0x3f6dbf35,
0x3f800000,0xbf800000,0x3f800000,0xbf800000,0x3f6d0000,0xbec43f35,0xbec4bf80,0x3f6d3f35,
0x3f350000,0x3f353f80,0xbf350000,0xbf35bf80,0x3ec40000,0x3f6d3f35,0x3f6d3f80,0x3ec43f35,
0x00000000,0x00000000,0x00000000,0x00000000,0xbec40000,0xbf6d3f35,0xbf6d3f80,0xbec43f35,
0x3f350000,0x3f35bf80,0xbf350000,0xbf353f80,0xbf6d0000,0x3ec43f35,0x3ec4bf80,0xbf6d3f35,
0x3f800000,0xbf800000,0x3f800000,0xbf800000,0xbf6d0000,0x3ec4bf35,0x3ec43f80,0xbf6dbf35,
0x3f350000,0x3f353f80,0xbf350000,0xbf35bf80,0xbec40000,0xbf6dbf35,0xbf6dbf80,0xbec4bf35,
0x00000000,0x00000000,0x00000000,0x00000000,0x3ec40000,0x3f6d3f35,0x3f6d3f80,0x3ec43f35,
0x3f350000,0x3f353f80,0xbf350000,0xbf35bf80,0x3f6d0000,0xbec43f35,0xbec4bf80,0x3f6d3f35,
0x3f800000,0xbf800000,0x3f800000,0xbf800000,0x3f6d0000,0xbec4bf35,0xbec43f80,0x3f6dbf35,
0x3f350000,0x3f35bf80,0xbf350000,0xbf353f80,0x3ec40000,0x3f6dbf35,0x3f6dbf80,0x3ec4bf35,
0x00000000,0x00000000,0x00000000,0x00000000,0xbec40000,0xbf6dbf35,0xbf6dbf80,0xbec4bf35,
0x3f350000,0x3f353f80,0xbf350000,0xbf35bf80,0xbf6d0000,0x3ec4bf35,0x3ec43f80,0xbf6dbf35,
0x3f800000,0xbf800000,0x3f800000,0xbf800000,0xbf6d0000,0x3ec43f35,0x3ec4bf80,0xbf6d3f35,
0x3f350000,0x3f35bf80,0xbf350000,0xbf353f80,0xbec40000,0xbf6d3f35,0xbf6d3f80,0xbec43f35,
0x00000000,0x00000000,0x00000000,0x00000000,0xbec40000,0xbf6d3f35,0xbf6d3f80,0xbec43f35,
0xbf350000,0xbf353f80,0x3f350000,0x3f35bf80,0xbf6d0000,0x3ec43f35,0x3ec4bf80,0xbf6d3f35,
0xbf800000,0x3f800000,0xbf800000,0x3f800000,0xbf6d0000,0x3ec4bf35,0x3ec43f80,0xbf6dbf35,
0xbf350000,0xbf35bf80,0x3f350000,0x3f353f80,0xbec40000,0xbf6dbf35,0xbf6dbf80,0xbec4bf35,
0x00000000,0x00000000,0x00000000,0x00000000,0x3ec40000,0x3f6dbf35,0x3f6dbf80,0x3ec4bf35,
0xbf350000,0xbf353f80,0x3f350000,0x3f35bf80,0x3f6d0000,0xbec4bf35,0xbec43f80,0x3f6dbf35,
0xbf800000,0x3f800000,0xbf800000,0x3f800000,0x3f6d0000,0xbec43f35,0xbec4bf80,0x3f6d3f35,
0xbf350000,0xbf35bf80,0x3f350000,0x3f353f80,0x3ec40000,0x3f6d3f35,0x3f6d3f80,0x3ec43f35,
0x3f803f80,0x3f803f80,0x3f803f80,0x3f803f80,0x3f6d3f80,0x3ec43f35,0xbec40000,0xbf6dbf35,
0x3f353f80,0xbf350000,0xbf35bf80,0x3f350000,0x3ec43f80,0xbf6dbf35,0x3f6d0000,0xbec43f35,
0x00003f80,0x0000bf80,0x00003f80,0x0000bf80,0xbec43f80,0x3f6dbf35,0xbf6d0000,0x3ec43f35,
0xbf353f80,0x3f350000,0x3f35bf80,0xbf350000,0xbf6d3f80,0xbec43f35,0x3ec40000,0x3f6dbf35,
0x3f803f80,0x3f803f80,0x3f803f80,0x3f803f80,0xbf6dbf80,0xbec4bf35,0x3ec40000,0x3f6d3f35,
0x3f353f80,0xbf350000,0xbf35bf80,0x3f350000,0xbec4bf80,0x3f6d3f35,0xbf6d0000,0x3ec4bf35,
0x00003f80,0x0000bf80,0x00003f80,0x0000bf80,0x3ec4bf80,0xbf6d3f35,0x3f6d0000,0xbec4bf35,
0xbf353f80,0x3f350000,0x3f35bf80,0xbf350000,0x3f6dbf80,0x3ec4bf35,0xbec40000,0xbf6d3f35,
0xbf803f80,0xbf803f80,0xbf803f80,0xbf803f80,0xbf6d3f80,0xbec43f35,0x3ec40000,0x3f6dbf35,
0xbf353f80,0x3f350000,0x3f35bf80,0xbf350000,0xbec43f80,0x3f6dbf35,0xbf6d0000,0x3ec43f35,
0x00003f80,0x0000bf80,0x00003f80,0x0000bf80,0x3ec43f80,0xbf6dbf35,0x3f6d0000,0xbec43f35,
0x3f353f80,0xbf350000,0xbf35bf80,0x3f350000,0x3f6d3f80,0x3ec43f35,0xbec40000,0xbf6dbf35,
0xbf803f80,0xbf803f80,0xbf803f80,0xbf803f80,0x3f6dbf80,0x3ec4bf35,0xbec40000,0xbf6d3f35,
0xbf353f80,0x3f350000,0x3f35bf80,0xbf350000,0x3ec4bf80,0xbf6d3f35,0x3f6d0000,0xbec4bf35,
0x00003f80,0x0000bf80,0x00003f80,0x0000bf80,0xbec4bf80,0x3f6d3f35,0xbf6d0000,0x3ec4bf35,
0x3f353f80,0xbf350000,0xbf35bf80,0x3f350000,0xbf6dbf80,0xbec4bf35,0x3ec40000,0x3f6d3f35,
0x3b003b00,0x3b003b00,0x3b003b00,0x3b003b00,0x3af83b00,0x3ace3ae7,0x3a843aac,0x39963a2c,
0x3ae23aff,0x3a153aa2,0xba71b949,0xbaf5bac6,0x3abe3afd,0xba2c39f9,0xbb00bace,0xba5bbadc,
0x3a8e3afb,0xbad5b9c8,0xba8ebafb,0x3ad539c8,0x3a2c3af8,0xbb00ba98,0x3a5bba84,0x3aac3afd,
0x39493af5,0xbac6bae2,0x3aff3a15,0xbaa23a71,0xb9963af1,0xb9f9bb00,0x3a983ae7,0xbadcbaac,
0x00000000,0x00000000,0x00000000,0x00000000,0x39f938c9,0x3a983a5b,0x3adc3abe,0x3afd3af1,
0x3a713949,0x3af53ac6,0x3ae23aff,0x3a153aa2,0x3aac3996,0x3af13af8,0x38c93a98,0xbae7ba84,
0x3ad539c8,0x3a8e3afb,0xbad5b9c8,0xba8ebafb,0x3af139f9,0xb8c93ace,0xbae7badc,0x3abeb996,
0x3aff3a15,0xbaa23a71,0xb949baf5,0x3ac63ae2,0x3afd3a2c,0xbaf838c9,0x3aceba5b,0xba843abe,
0xba443aed,0x3a44baed,0xba443aed,0x3a44baed,0xba983ae7,0x3adcbaac,0xbafd3a2c,0x3af838c9,
0xbac63ae2,0x3affba15,0xbaa2ba71,0xb9493af5,0xbae73adc,0x3abe3996,0x3a2cbaf8,0xbb003a98,
0xbafb3ad5,0x39c83a8e,0x3afbbad5,0xb9c8ba8e,0xbb003ace,0xba5b3adc,0x3aacb996,0x3af1baf8,
0xbaf53ac6,0xbae23aff,0xba153aa2,0x3a71b949,0xbadc3abe,0xbafd3af1,0xbaf83b00,0xbace3ae7,
0x3aed3a44,0xbaedba44,0x3aed3a44,0xbaedba44,0x3ace3a5b,0xba84babe,0x39963af1,0x39f9bb00,
0x3aa23a71,0x3949baf5,0xbac63ae2,0x3affba15,0x3a5b3a84,0x3aacbafd,0xbaf139f9,0x38c93ace,
0x39c83a8e,0x3afbbad5,0xb9c8ba8e,0xbafb3ad5,0xb8c93a98,0x3ae7ba84,0x3abebafd,0xba2cb9f9,
0xba153aa2,0x3a71b949,0x3af5bac6,0x3ae2baff,0xba843aac,0xb9963a2c,0x39f9b8c9,0x3a98ba5b,
0xbab53ab5,0xbab53ab5,0xbab53ab5,0xbab53ab5,0xba843aac,0xb9963a2c,0x39f9b8c9,0x3a98ba5b,
0xba153aa2,0x3a71b949,0x3af5bac6,0x3ae2baff,0xb8c93a98,0x3ae7ba84,0x3abebafd,0xba2cb9f9,
0x39c83a8e,0x3afbbad5,0xb9c8ba8e,0xbafb3ad5,0x3a5b3a84,0x3aacbafd,0xbaf139f9,0x38c93ace,
0x3aa23a71,0x3949baf5,0xbac63ae2,0x3affba15,0x3ace3a5b,0xba84babe,0x39963af1,0x39f9bb00,
0xbab53ab5,0xbab53ab5,0xbab53ab5,0xbab53ab5,0xbadc3abe,0xbafd3af1,0xbaf83b00,0xbace3ae7,
0xbaf53ac6,0xbae23aff,0xba153aa2,0x3a71b949,0xbb003ace,0xba5b3adc,0x3aacb996,0x3af1baf8,
0xbafb3ad5,0x39c83a8e,0x3afbbad5,0xb9c8ba8e,0xbae73adc,0x3abe3996,0x3a2cbaf8,0xbb003a98,
0xbac63ae2,0x3affba15,0xbaa2ba71,0xb9493af5,0xba983ae7,0x3adcbaac,0xbafd3a2c,0x3af838c9,
0x3aed3a44,0xbaedba44,0x3aed3a44,0xbaedba44,0x3afd3a2c,0xbaf838c9,0x3aceba5b,0xba843abe,
0x3aff3a15,0xbaa23a71,0xb949baf5,0x3ac63ae2,0x3af139f9,0xb8c93ace,0xbae7badc,0x3abeb996,
0x3ad539c8,0x3a8e3afb,0xbad5b9c8,0xba8ebafb,0x3aac3996,0x3af13af8,0x38c93a98,0xbae7ba84,
0x3a713949,0x3af53ac6,0x3ae23aff,0x3a153aa2,0x39f938c9,0x3a983a5b,0x3adc3abe,0x3afd3af1,
0xba443aed,0x3a44baed,0xba443aed,0x3a44baed,0xb9963af1,0xb9f9bb00,0x3a983ae7,0xbadcbaac,
0x39493af5,0xbac6bae2,0x3aff3a15,0xbaa23a71,0x3a2c3af8,0xbb00ba98,0x3a5bba84,0x3aac3afd,
0x3a8e3afb,0xbad5b9c8,0xba8ebafb,0x3ad539c8,0x3abe3afd,0xba2c39f9,0xbb00bace,0xba5bbadc,
0x3ae23aff,0x3a153aa2,0xba71b949,0xbaf5bac6,0x3af83b00,0x3ace3ae7,0x3a843aac,0x39963a2c,
0x3b003b00,0x3b003b00,0x3b003b00,0x3b003b00,0xb9f9b8c9,0xba98ba5b,0xbadcbabe,0xbafdbaf1,
0xbae2baff,0xba15baa2,0x3a713949,0x3af53ac6,0x3aac3996,0x3af13af8,0x38c93a98,0xbae7ba84,
0x3a8e3afb,0xbad5b9c8,0xba8ebafb,0x3ad539c8,0xbaf1b9f9,0x38c9bace,0x3ae73adc,0xbabe3996,
0xb949baf5,0x3ac63ae2,0xbaffba15,0x3aa2ba71,0x3afd3a2c,0xbaf838c9,0x3aceba5b,0xba843abe,
0x00000000,0x00000000,0x00000000,0x00000000,0x3af83b00,0x3ace3ae7,0x3a843aac,0x39963a2c,
0xba71b949,0xbaf5bac6,0xbae2baff,0xba15baa2,0xbabebafd,0x3a2cb9f9,0x3b003ace,0x3a5b3adc,
0x3ad539c8,0x3a8e3afb,0xbad5b9c8,0xba8ebafb,0x3a2c3af8,0xbb00ba98,0x3a5bba84,0x3aac3afd,
0xbaffba15,0x3aa2ba71,0x39493af5,0xbac6bae2,0x3996baf1,0x39f93b00,0xba98bae7,0x3adc3aac,
0xba443aed,0x3a44baed,0xba443aed,0x3a44baed,0xbaceba5b,0x3a843abe,0xb996baf1,0xb9f93b00,
0x3ac6bae2,0xbaff3a15,0x3aa23a71,0x3949baf5,0x3a5b3a84,0x3aacbafd,0xbaf139f9,0x38c93ace,
0xbafb3ad5,0x39c83a8e,0x3afbbad5,0xb9c8ba8e,0x38c9ba98,0xbae73a84,0xbabe3afd,0x3a2c39f9,
0x3af5bac6,0x3ae2baff,0x3a15baa2,0xba713949,0xba843aac,0xb9963a2c,0x39f9b8c9,0x3a98ba5b,
0x3aed3a44,0xbaedba44,0x3aed3a44,0xbaedba44,0xba983ae7,0x3adcbaac,0xbafd3a2c,0x3af838c9,
0xbaa2ba71,0xb9493af5,0x3ac6bae2,0xbaff3a15,0x3ae7badc,0xbabeb996,0xba2c3af8,0x3b00ba98,
0x39c83a8e,0x3afbbad5,0xb9c8ba8e,0xbafb3ad5,0xbb003ace,0xba5b3adc,0x3aacb996,0x3af1baf8,
0x3a15baa2,0xba713949,0xbaf53ac6,0xbae23aff,0x3adcbabe,0x3afdbaf1,0x3af8bb00,0x3acebae7,
0xbab53ab5,0xbab53ab5,0xbab53ab5,0xbab53ab5,0x3adcbabe,0x3afdbaf1,0x3af8bb00,0x3acebae7,
0x3a15baa2,0xba713949,0xbaf53ac6,0xbae23aff,0xbb003ace,0xba5b3adc,0x3aacb996,0x3af1baf8,
0x39c83a8e,0x3afbbad5,0xb9c8ba8e,0xbafb3ad5,0x3ae7badc,0xbabeb996,0xba2c3af8,0x3b00ba98,
0xbaa2ba71,0xb9493af5,0x3ac6bae2,0xbaff3a15,0xba983ae7,0x3adcbaac,0xbafd3a2c,0x3af838c9,
0xbab53ab5,0xbab53ab5,0xbab53ab5,0xbab53ab5,0xba843aac,0xb9963a2c,0x39f9b8c9,0x3a98ba5b,
0x3af5bac6,0x3ae2baff,0x3a15baa2,0xba713949,0x38c9ba98,0xbae73a84,0xbabe3afd,0x3a2c39f9,
0xbafb3ad5,0x39c83a8e,0x3afbbad5,0xb9c8ba8e,0x3a5b3a84,0x3aacbafd,0xbaf139f9,0x38c93ace,
0x3ac6bae2,0xbaff3a15,0x3aa23a71,0x3949baf5,0xbaceba5b,0x3a843abe,0xb996baf1,0xb9f93b00,
0x3aed3a44,0xbaedba44,0x3aed3a44,0xbaedba44,0x3996baf1,0x39f93b00,0xba98bae7,0x3adc3aac,
0xbaffba15,0x3aa2ba71,0x39493af5,0xbac6bae2,0x3a2c3af8,0xbb00ba98,0x3a5bba84,0x3aac3afd,
0x3ad539c8,0x3a8e3afb,0xbad5b9c8,0xba8ebafb,0xbabebafd,0x3a2cb9f9,0x3b003ace,0x3a5b3adc,
0xba71b949,0xbaf5bac6,0xbae2baff,0xba15baa2,0x3af83b00,0x3ace3ae7,0x3a843aac,0x39963a2c,
0xba443aed,0x3a44baed,0xba443aed,0x3a44baed,0x3afd3a2c,0xbaf838c9,0x3aceba5b,0xba843abe,
0xb949baf5,0x3ac63ae2,0xbaffba15,0x3aa2ba71,0xbaf1b9f9,0x38c9bace,0x3ae73adc,0xbabe3996,
0x3a8e3afb,0xbad5b9c8,0xba8ebafb,0x3ad539c8,0x3aac3996,0x3af13af8,0x38c93a98,0xbae7ba84,
0xbae2baff,0xba15baa2,0x3a713949,0x3af53ac6,0xb9f9b8c9,0xba98ba5b,0xbadcbabe,0xbafdbaf1,
0x3b003b00,0x3b003b00,0x3b003b00,0x3b003b00,0xbaf8bb00,0xbacebae7,0xba84baac,0xb996ba2c,
0x3ae23aff,0x3a153aa2,0xba71b949,0xbaf5bac6,0xbabebafd,0x3a2cb9f9,0x3b003ace,0x3a5b3adc,
0x3a8e3afb,0xbad5b9c8,0xba8ebafb,0x3ad539c8,0xba2cbaf8,0x3b003a98,0xba5b3a84,0xbaacbafd,
0x39493af5,0xbac6bae2,0x3aff3a15,0xbaa23a71,0x3996baf1,0x39f93b00,0xba98bae7,0x3adc3aac,
0x00000000,0x00000000,0x00000000,0x00000000,0xb9f9b8c9,0xba98ba5b,0xbadcbabe,0xbafdbaf1,
0x3a713949,0x3af53ac6,0x3ae23aff,0x3a153aa2,0xbaacb996,0xbaf1baf8,0xb8c9ba98,0x3ae73a84,
0x3ad539c8,0x3a8e3afb,0xbad5b9c8,0xba8ebafb,0xbaf1b9f9,0x38c9bace,0x3ae73adc,0xbabe3996,
0x3aff3a15,0xbaa23a71,0xb949baf5,0x3ac63ae2,0xbafdba2c,0x3af8b8c9,0xbace3a5b,0x3a84babe,
0xba443aed,0x3a44baed,0xba443aed,0x3a44baed,0x3a98bae7,0xbadc3aac,0x3afdba2c,0xbaf8b8c9,
0xbac63ae2,0x3affba15,0xbaa2ba71,0xb9493af5,0x3ae7badc,0xbabeb996,0xba2c3af8,0x3b00ba98,
0xbafb3ad5,0x39c83a8e,0x3afbbad5,0xb9c8ba8e,0x3b00bace,0x3a5bbadc,0xbaac3996,0xbaf13af8,
0xbaf53ac6,0xbae23aff,0xba153aa2,0x3a71b949,0x3adcbabe,0x3afdbaf1,0x3af8bb00,0x3acebae7,
0x3aed3a44,0xbaedba44,0x3aed3a44,0xbaedba44,0xbaceba5b,0x3a843abe,0xb996baf1,0xb9f93b00,
0x3aa23a71,0x3949baf5,0xbac63ae2,0x3affba15,0xba5bba84,0xbaac3afd,0x3af1b9f9,0xb8c9bace,
0x39c83a8e,0x3afbbad5,0xb9c8ba8e,0xbafb3ad5,0x38c9ba98,0xbae73a84,0xbabe3afd,0x3a2c39f9,
0xba153aa2,0x3a71b949,0x3af5bac6,0x3ae2baff,0x3a84baac,0x3996ba2c,0xb9f938c9,0xba983a5b,
0xbab53ab5,0xbab53ab5,0xbab53ab5,0xbab53ab5,0x3a84baac,0x3996ba2c,0xb9f938c9,0xba983a5b,
0xba153aa2,0x3a71b949,0x3af5bac6,0x3ae2baff,0x38c9ba98,0xbae73a84,0xbabe3afd,0x3a2c39f9,
0x39c83a8e,0x3afbbad5,0xb9c8ba8e,0xbafb3ad5,0xba5bba84,0xbaac3afd,0x3af1b9f9,0xb8c9bace,
0x3aa23a71,0x3949baf5,0xbac63ae2,0x3affba15,0xbaceba5b,0x3a843abe,0xb996baf1,0xb9f93b00,
0xbab53ab5,0xbab53ab5,0xbab53ab5,0xbab53ab5,0x3adcbabe,0x3afdbaf1,0x3af8bb00,0x3acebae7,
0xbaf53ac6,0xbae23aff,0xba153aa2,0x3a71b949,0x3b00bace,0x3a5bbadc,0xbaac3996,0xbaf13af8,
0xbafb3ad5,0x39c83a8e,0x3afbbad5,0xb9c8ba8e,0x3ae7badc,0xbabeb996,0xba2c3af8,0x3b00ba98,
0xbac63ae2,0x3affba15,0xbaa2ba71,0xb9493af5,0x3a98bae7,0xbadc3aac,0x3afdba2c,0xbaf8b8c9,
0x3aed3a44,0xbaedba44,0x3aed3a44,0xbaedba44,0xbafdba2c,0x3af8b8c9,0xbace3a5b,0x3a84babe,
0x3aff3a15,0xbaa23a71,0xb949baf5,0x3ac63ae2,0xbaf1b9f9,0x38c9bace,0x3ae73adc,0xbabe3996,
0x3ad539c8,0x3a8e3afb,0xbad5b9c8,0xba8ebafb,0xbaacb996,0xbaf1baf8,0xb8c9ba98,0x3ae73a84,
0x3a713949,0x3af53ac6,0x3ae23aff,0x3a153aa2,0xb9f9b8c9,0xba98ba5b,0xbadcbabe,0xbafdbaf1,
0xba443aed,0x3a44baed,0xba443aed,0x3a44baed,0x3996baf1,0x39f93b00,0xba98bae7,0x3adc3aac,
0x39493af5,0xbac6bae2,0x3aff3a15,0xbaa23a71,0xba2cbaf8,0x3b003a98,0xba5b3a84,0xbaacbafd,
0x3a8e3afb,0xbad5b9c8,0xba8ebafb,0x3ad539c8,0xbabebafd,0x3a2cb9f9,0x3b003ace,0x3a5b3adc,
0x3ae23aff,0x3a153aa2,0xba71b949,0xbaf5bac6,0xbaf8bb00,0xbacebae7,0xba84baac,0xb996ba2c,
0x3b003b00,0x3b003b00,0x3b003b00,0x3b003b00,0x39f938c9,0x3a983a5b,0x3adc3abe,0x3afd3af1,
0xbae2baff,0xba15baa2,0x3a713949,0x3af53ac6,0xbaacb996,0xbaf1baf8,0xb8c9ba98,0x3ae73a84,
0x3a8e3afb,0xbad5b9c8,0xba8ebafb,0x3ad539c8,0x3af139f9,0xb8c93ace,0xbae7badc,0x3abeb996,
0xb949baf5,0x3ac63ae2,0xbaffba15,0x3aa2ba71,0xbafdba2c,0x3af8b8c9,0xbace3a5b,0x3a84babe,
0x00000000,0x00000000,0x00000000,0x00000000,0xbaf8bb00,0xbacebae7,0xba84baac,0xb996ba2c,
0xba71b949,0xbaf5bac6,0xbae2baff,0xba15baa2,0x3abe3afd,0xba2c39f9,0xbb00bace,0xba5bbadc,
0x3ad539c8,0x3a8e3afb,0xbad5b9c8,0xba8ebafb,0xba2cbaf8,0x3b003a98,0xba5b3a84,0xbaacbafd,
0xbaffba15,0x3aa2ba71,0x39493af5,0xbac6bae2,0xb9963af1,0xb9f9bb00,0x3a983ae7,0xbadcbaac,
0xba443aed,0x3a44baed,0xba443aed,0x3a44baed,0x3ace3a5b,0xba84babe,0x39963af1,0x39f9bb00,
0x3ac6bae2,0xbaff3a15,0x3aa23a71,0x3949baf5,0xba5bba84,0xbaac3afd,0x3af1b9f9,0xb8c9bace,
0xbafb3ad5,0x39c83a8e,0x3afbbad5,0xb9c8ba8e,0xb8c93a98,0x3ae7ba84,0x3abebafd,0xba2cb9f9,
0x3af5bac6,0x3ae2baff,0x3a15baa2,0xba713949,0x3a84baac,0x3996ba2c,0xb9f938c9,0xba983a5b,
0x3aed3a44,0xbaedba44,0x3aed3a44,0xbaedba44,0x3a98bae7,0xbadc3aac,0x3afdba2c,0xbaf8b8c9,
0xbaa2ba71,0xb9493af5,0x3ac6bae2,0xbaff3a15,0xbae73adc,0x3abe3996,0x3a2cbaf8,0xbb003a98,
0x39c83a8e,0x3afbbad5,0xb9c8ba8e,0xbafb3ad5,0x3b00bace,0x3a5bbadc,0xbaac3996,0xbaf13af8,
0x3a15baa2,0xba713949,0xbaf53ac6,0xbae23aff,0xbadc3abe,0xbafd3af1,0xbaf83b00,0xbace3ae7,
0xbab53ab5,0xbab53ab5,0xbab53ab5,0xbab53ab5,0xbadc3abe,0xbafd3af1,0xbaf83b00,0xbace3ae7,
0x3a15baa2,0xba713949,0xbaf53ac6,0xbae23aff,0x3b00bace,0x3a5bbadc,0xbaac3996,0xbaf13af8,
0x39c83a8e,0x3afbbad5,0xb9c8ba8e,0xbafb3ad5,0xbae73adc,0x3abe3996,0x3a2cbaf8,0xbb003a98,
0xbaa2ba71,0xb9493af5,0x3ac6bae2,0xbaff3a15,0x3a98bae7,0xbadc3aac,0x3afdba2c,0xbaf8b8c9,
0xbab53ab5,0xbab53ab5,0xbab53ab5,0xbab53ab5,0x3a84baac,0x3996ba2c,0xb9f938c9,0xba983a5b,
0x3af5bac6,0x3ae2baff,0x3a15baa2,0xba713949,0xb8c93a98,0x3ae7ba84,0x3abebafd,0xba2cb9f9,
0xbafb3ad5,0x39c83a8e,0x3afbbad5,0xb9c8ba8e,0xba5bba84,0xbaac3afd,0x3af1b9f9,0xb8c9bace,
0x3ac6bae2,0xbaff3a15,0x3aa23a71,0x3949baf5,0x3ace3a5b,0xba84babe,0x39963af1,0x39f9bb00,
0x3aed3a44,0xbaedba44,0x3aed3a44,0xbaedba44,0xb9963af1,0xb9f9bb00,0x3a983ae7,0xbadcbaac,
0xbaffba15,0x3aa2ba71,0x39493af5,0xbac6bae2,0xba2cbaf8,0x3b003a98,0xba5b3a84,0xbaacbafd,
0x3ad539c8,0x3a8e3afb,0xbad5b9c8,0xba8ebafb,0x3abe3afd,0xba2c39f9,0xbb00bace,0xba5bbadc,
0xba71b949,0xbaf5bac6,0xbae2baff,0xba15baa2,0xbaf8bb00,0xbacebae7,0xba84baac,0xb996ba2c,
0xba443aed,0x3a44baed,0xba443aed,0x3a44baed,0xbafdba2c,0x3af8b8c9,0xbace3a5b,0x3a84babe,
0xb949baf5,0x3ac63ae2,0xbaffba15,0x3aa2ba71,0x3af139f9,0xb8c93ace,0xbae7badc,0x3abeb996,
0x3a8e3afb,0xbad5b9c8,0xba8ebafb,0x3ad539c8,0xbaacb996,0xbaf1baf8,0xb8c9ba98,0x3ae73a84,
0xbae2baff,0xba15baa2,0x3a713949,0x3af53ac6,0x39f938c9,0x3a983a5b,0x3adc3abe,0x3afd3af1,
};

__device__ const __align__(128) uint32_t CTAB[1536] = {
0x3f803f80,0x3d490000,0x3f6d3f67,0x3ec43edb,0x3f7d3f7f,0x3e163dc9,0x3f623f5c,0x3ef13f04,
0x3f783f7b,0x3e793e48,0x3f553f4e,0x3f0e3f18,0x3f713f75,0x3eac3e95,0x3f463f3e,0x3f223f2c,
0x3f783f80,0x3e790000,0xbec4bf18,0x3f6d3f4e,0x3f3e3f62,0x3f2c3ef1,0xbf46bf67,0x3f223edb,
0x3eac3f0e,0x3f713f55,0xbf7bbf80,0x3e48bd49,0xbe163dc9,0x3f7d3f7f,0xbf75bf5c,0xbe95bf04,
0x3f673f80,0x3edb0000,0xbf6dbf2c,0xbec4bf3e,0x3e793f22,0x3f783f46,0xbe953e16,0xbf75bf7d,
0xbf18be48,0x3f4e3f7b,0x3f0e3f5c,0xbf55bf04,0xbf80bf62,0x3d493ef1,0x3f7f3f71,0xbdc93eac,
0x3f4e3f80,0x3f180000,0x3ec43f5c,0xbf6dbf04,0xbeac3e95,0x3f713f75,0x3f7f3f3e,0x3dc93f2c,
0xbf80bf55,0xbd493f0e,0x3e48bedb,0x3f7b3f67,0xbe79bf46,0xbf78bf22,0xbf62bf7d,0x3ef1be16,
0x3f2c3f80,0x3f3e0000,0x3f6d3eac,0x3ec43f71,0xbf4ebdc9,0x3f183f7f,0xbef1bf78,0x3f623e79,
0xbf04bf7b,0xbf5cbe48,0xbf55be16,0xbf0ebf7d,0x3f673e95,0xbedbbf75,0x3f223f80,0xbf46bd49,
0x3f043f80,0x3f5c0000,0xbec4bf7d,0x3f6d3e16,0xbf80bef1,0x3d493f62,0xbf223eac,0xbf46bf71,
0x3edbbf0e,0xbf67bf55,0x3f7b3f2c,0xbe483f3e,0x3f183f7f,0x3f4ebdc9,0xbe95bf78,0x3f753e79,
0x3eac3f80,0x3f710000,0xbf6d3d49,0xbec4bf80,0xbf5cbf46,0xbf043f22,0x3f753f18,0xbe953f4e,
0x3f7d3e48,0xbe16bf7b,0xbf0ebf78,0x3f55be79,0xbf2c3ef1,0x3f3e3f62,0xbdc93f67,0xbf7fbedb,
0x3e163f80,0x3f7d0000,0x3ec43f78,0xbf6d3e79,0xbedbbf75,0xbf673e95,0xbdc9bf80,0x3f7f3d49,
0x3f2c3f55,0x3f3ebf0e,0xbe483f71,0xbf7bbeac,0xbf5cbf22,0xbf043f46,0x3ef1bf4e,0x3f623f18,
0xbd493f80,0x3f800000,0x3f6dbedb,0x3ec43f67,0x3e16bf7f,0xbf7dbdc9,0xbf623f04,0xbef1bf5c,
0xbe793f7b,0x3f783e48,0x3f55bf18,0x3f0e3f4e,0x3eacbf75,0xbf71be95,0xbf463f2c,0xbf22bf3e,
0xbe793f80,0x3f780000,0xbec4bf4e,0x3f6dbf18,0x3f2cbf62,0xbf3ebef1,0x3f463edb,0xbf223f67,
0xbf713f0e,0x3eac3f55,0xbf7b3d49,0x3e48bf80,0x3f7dbdc9,0x3e16bf7f,0x3f75bf04,0x3e953f5c,
0xbedb3f80,0x3f670000,0xbf6d3f3e,0xbec4bf2c,0x3f78bf22,0xbe79bf46,0x3e95bf7d,0x3f75be16,
0xbf4ebe48,0xbf183f7b,0x3f0e3f04,0xbf553f5c,0x3d493f62,0x3f80bef1,0xbf7f3eac,0x3dc9bf71,
0xbf183f80,0x3f4e0000,0x3ec43f04,0xbf6d3f5c,0x3f71be95,0x3eacbf75,0xbf7f3f2c,0xbdc9bf3e,
0x3d49bf55,0xbf803f0e,0x3e48bf67,0x3f7bbedb,0xbf783f46,0x3e793f22,0x3f62be16,0xbef13f7d,
0xbf3e3f80,0x3f2c0000,0x3f6dbf71,0x3ec43eac,0x3f183dc9,0x3f4ebf7f,0x3ef13e79,0xbf623f78,
0x3f5cbf7b,0xbf04be48,0xbf553f7d,0xbf0ebe16,0xbedbbe95,0xbf673f75,0xbf22bd49,0x3f46bf80,
0xbf5c3f80,0x3f040000,0xbec4be16,0x3f6dbf7d,0x3d493ef1,0x3f80bf62,0x3f22bf71,0x3f46beac,
0x3f67bf0e,0x3edbbf55,0x3f7bbf3e,0xbe483f2c,0x3f4ebf7f,0xbf183dc9,0x3e953e79,0xbf753f78,
0xbf713f80,0x3eac0000,0xbf6d3f80,0xbec43d49,0xbf043f46,0x3f5cbf22,0xbf753f4e,0x3e95bf18,
0x3e163e48,0x3f7dbf7b,0xbf0e3e79,0x3f55bf78,0x3f3ebef1,0x3f2cbf62,0x3dc9bedb,0x3f7fbf67,
0xbf7d3f80,0x3e160000,0x3ec4be79,0xbf6d3f78,0xbf673f75,0x3edbbe95,0x3dc93d49,0xbf7f3f80,
0xbf3e3f55,0x3f2cbf0e,0xbe483eac,0xbf7b3f71,0xbf043f22,0x3f5cbf46,0xbef13f18,0xbf623f4e,
0xbf803f80,0xbd490000,0x3f6dbf67,0x3ec4bedb,0xbf7d3f7f,0xbe163dc9,0x3f62bf5c,0x3ef1bf04,
0xbf783f7b,0xbe793e48,0x3f55bf4e,0x3f0ebf18,0xbf713f75,0xbeac3e95,0x3f46bf3e,0x3f22bf2c,
0xbf783f80,0xbe790000,0xbec43f18,0x3f6dbf4e,0xbf3e3f62,0xbf2c3ef1,0xbf463f67,0x3f22bedb,
0xbeac3f0e,0xbf713f55,0xbf7b3f80,0x3e483d49,0x3e163dc9,0xbf7d3f7f,0xbf753f5c,0xbe953f04,
0xbf673f80,0xbedb0000,0xbf6d3f2c,0xbec43f3e,0xbe793f22,0xbf783f46,0xbe95be16,0xbf753f7d,
0x3f18be48,0xbf4e3f7b,0x3f0ebf5c,0xbf553f04,0x3f80bf62,0xbd493ef1,0x3f7fbf71,0xbdc9beac,
0xbf4e3f80,0xbf180000,0x3ec4bf5c,0xbf6d3f04,0x3eac3e95,0xbf713f75,0x3f7fbf3e,0x3dc9bf2c,
0x3f80bf55,0x3d493f0e,0x3e483edb,0x3f7bbf67,0x3e79bf46,0x3f78bf22,0xbf623f7d,0x3ef13e16,
0xbf2c3f80,0xbf3e0000,0x3f6dbeac,0x3ec4bf71,0x3f4ebdc9,0xbf183f7f,0xbef13f78,0x3f62be79,
0x3f04bf7b,0x3f5cbe48,0xbf553e16,0xbf0e3f7d,0xbf673e95,0x3edbbf75,0x3f22bf80,0xbf463d49,
0xbf043f80,0xbf5c0000,0xbec43f7d,0x3f6dbe16,0x3f80bef1,0xbd493f62,0xbf22beac,0xbf463f71,
0xbedbbf0e,0x3f67bf55,0x3f7bbf2c,0xbe48bf3e,0xbf183f7f,0xbf4ebdc9,0xbe953f78,0x3f75be79,
0xbeac3f80,0xbf710000,0xbf6dbd49,0xbec43f80,0x3f5cbf46,0x3f043f22,0x3f75bf18,0xbe95bf4e,
0xbf7d3e48,0x3e16bf7b,0xbf0e3f78,0x3f553e79,0x3f2c3ef1,0xbf3e3f62,0xbdc9bf67,0xbf7f3edb,
0xbe163f80,0xbf7d0000,0x3ec4bf78,0xbf6dbe79,0x3edbbf75,0x3f673e95,0xbdc93f80,0x3f7fbd49,
0xbf2c3f55,0xbf3ebf0e,0xbe48bf71,0xbf7b3eac,0x3f5cbf22,0x3f043f46,0x3ef13f4e,0x3f62bf18,
0x3d493f80,0xbf800000,0x3f6d3edb,0x3ec4bf67,0xbe16bf7f,0x3f7dbdc9,0xbf62bf04,0xbef13f5c,
0x3e793f7b,0xbf783e48,0x3f553f18,0x3f0ebf4e,0xbeacbf75,0x3f71be95,0xbf46bf2c,0xbf223f3e,
0x3e793f80,0xbf780000,0xbec43f4e,0x3f6d3f18,0xbf2cbf62,0x3f3ebef1,0x3f46bedb,0xbf22bf67,
0x3f713f0e,0xbeac3f55,0xbf7bbd49,0x3e483f80,0xbf7dbdc9,0xbe16bf7f,0x3f753f04,0x3e95bf5c,
0x3edb3f80,0xbf670000,0xbf6dbf3e,0xbec43f2c,0xbf78bf22,0x3e79bf46,0x3e953f7d,0x3f753e16,
0x3f4ebe48,0x3f183f7b,0x3f0ebf04,0xbf55bf5c,0xbd493f62,0xbf80bef1,0xbf7fbeac,0x3dc93f71,
0x3f183f80,0xbf4e0000,0x3ec4bf04,0xbf6dbf5c,0xbf71be95,0xbeacbf75,0xbf7fbf2c,0xbdc93f3e,
0xbd49bf55,0x3f803f0e,0x3e483f67,0x3f7b3edb,0x3f783f46,0xbe793f22,0x3f623e16,0xbef1bf7d,
0x3f3e3f80,0xbf2c0000,0x3f6d3f71,0x3ec4beac,0xbf183dc9,0xbf4ebf7f,0x3ef1be79,0xbf62bf78,
0xbf5cbf7b,0x3f04be48,0xbf55bf7d,0xbf0e3e16,0x3edbbe95,0x3f673f75,0xbf223d49,0x3f463f80,
0x3f5c3f80,0xbf040000,0xbec43e16,0x3f6d3f7d,0xbd493ef1,0xbf80bf62,0x3f223f71,0x3f463eac,
0xbf67bf0e,0xbedbbf55,0x3f7b3f3e,0xbe48bf2c,0xbf4ebf7f,0x3f183dc9,0x3e95be79,0xbf75bf78,
0x3f713f80,0xbeac0000,0xbf6dbf80,0xbec4bd49,0x3f043f46,0xbf5cbf22,0xbf75bf4e,0x3e953f18,
0xbe163e48,0xbf7dbf7b,0xbf0ebe79,0x3f553f78,0xbf3ebef1,0xbf2cbf62,0x3dc93edb,0x3f7f3f67,
0x3f7d3f80,0xbe160000,0x3ec43e79,0xbf6dbf78,0x3f673f75,0xbedbbe95,0x3dc9bd49,0xbf7fbf80,
0x3f3e3f55,0xbf2cbf0e,0xbe48beac,0xbf7bbf71,0x3f043f22,0xbf5cbf46,0xbef1bf18,0xbf62bf4e,
0x3f183f22,0x3f4e3f46,0x3e953e79,0x3f753f78,0x3f2c3f35,0x3f3e3f35,0x3ec43eac,0x3f6d3f71,
0x3edb3ef1,0x3f673f62,0x3dc93d49,0x3f7f3f80,0x3f043f0e,0x3f5c3f55,0x3e483e16,0x3f7b3f7d,
0xbd49be95,0xbf80bf75,0x3f7f3f71,0x3dc93eac,0xbf04bf35,0xbf5cbf35,0x3f6d3f7d,0xbec4be16,
0x3f4e3f22,0xbf18bf46,0x3ef13e79,0x3f623f78,0x3edb3e48,0xbf67bf7b,0x3f553f2c,0x3f0e3f3e,
0xbf04bdc9,0x3f5c3f7f,0x3ef13f4e,0xbf62bf18,0x3eac3f35,0x3f713f35,0xbec43d49,0xbf6dbf80,
0xbf3ebf75,0xbf2cbe95,0x3f463edb,0x3f223f67,0xbf7dbf55,0x3e163f0e,0x3f7b3f78,0xbe483e79,
0x3f673ef1,0xbedbbf62,0xbf22bd49,0xbf46bf80,0xbe16bf35,0xbf7dbf35,0xbf6dbf78,0x3ec4be79,
0xbf043dc9,0x3f5c3f7f,0x3f753f18,0x3e953f4e,0x3f2c3f7b,0x3f3e3e48,0x3f0e3f71,0xbf55beac,
0xbf7dbf46,0xbe163f22,0xbf75bf5c,0x3e95bf04,0xbd493f35,0x3f803f35,0x3ec4bedb,0x3f6d3f67,
0x3f713f62,0x3eacbef1,0x3f7f3f3e,0xbdc93f2c,0x3e79bf0e,0xbf78bf55,0xbe483f18,0xbf7bbf4e,
0x3f3e3f75,0x3f2cbe95,0xbdc9bf67,0x3f7f3edb,0x3e79bf35,0xbf78bf35,0x3f6d3f4e,0xbec43f18,
0x3e16bf46,0xbf7dbf22,0x3f623f5c,0xbef13f04,0xbf71be48,0x3eac3f7b,0xbf553d49,0xbf0ebf80,
0xbe79bf7f,0xbf78bdc9,0x3f62be16,0x3ef13f7d,0xbedb3f35,0x3f673f35,0xbec43f3e,0xbf6dbf2c,
0xbf80be95,0x3d493f75,0x3f223f71,0xbf463eac,0x3f4e3f55,0x3f18bf0e,0xbf7bbf04,0x3e48bf5c,
0xbeac3f62,0x3f713ef1,0x3f463f3e,0xbf223f2c,0x3f18bf35,0xbf4ebf35,0xbf6dbf04,0x3ec4bf5c,
0x3e793f7f,0x3f78bdc9,0x3e953f7d,0xbf753e16,0x3d49bf7b,0xbf80be48,0xbf0ebf67,0x3f55bedb,
0x3f4ebf22,0xbf18bf46,0xbe953f78,0xbf75be79,0xbf3e3f35,0x3f2c3f35,0x3ec4bf71,0x3f6d3eac,
0x3f67bef1,0xbedbbf62,0xbdc93f80,0xbf7fbd49,0xbf5c3f0e,0x3f043f55,0x3e48bf7d,0x3f7b3e16,
0xbf803e95,0x3d493f75,0xbf7f3eac,0xbdc9bf71,0x3f5cbf35,0xbf04bf35,0x3f6d3e16,0xbec43f7d,
0xbf18bf22,0xbf4e3f46,0xbef13f78,0xbf62be79,0x3f673e48,0x3edbbf7b,0x3f55bf3e,0x3f0e3f2c,
0x3f5c3dc9,0x3f04bf7f,0xbef1bf18,0x3f62bf4e,0xbf713f35,0x3eac3f35,0xbec43f80,0xbf6d3d49,
0xbf2c3f75,0x3f3e3e95,0xbf463f67,0xbf22bedb,0xbe16bf55,0xbf7d3f0e,0x3f7bbe79,0xbe483f78,
0xbedbbef1,0xbf673f62,0x3f22bf80,0x3f463d49,0x3f7dbf35,0xbe16bf35,0xbf6d3e79,0x3ec4bf78,
0x3f5cbdc9,0x3f04bf7f,0xbf753f4e,0xbe95bf18,0xbf3e3f7b,0x3f2c3e48,0x3f0e3eac,0xbf553f71,
0xbe163f46,0x3f7dbf22,0x3f75bf04,0xbe953f5c,0xbf803f35,0xbd493f35,0x3ec4bf67,0x3f6dbedb,
0x3eacbf62,0xbf713ef1,0xbf7f3f2c,0x3dc9bf3e,0x3f78bf0e,0x3e79bf55,0xbe483f4e,0xbf7b3f18,
0x3f2cbf75,0xbf3e3e95,0x3dc93edb,0xbf7f3f67,0x3f78bf35,0x3e79bf35,0x3f6dbf18,0xbec43f4e,
0xbf7d3f46,0xbe163f22,0xbf623f04,0x3ef1bf5c,0xbeacbe48,0xbf713f7b,0xbf553f80,0xbf0e3d49,
0xbf783f7f,0x3e793dc9,0xbf623f7d,0xbef13e16,0xbf673f35,0xbedb3f35,0xbec43f2c,0xbf6d3f3e,
0x3d493e95,0x3f80bf75,0xbf223eac,0x3f46bf71,0xbf183f55,0x3f4ebf0e,0xbf7b3f5c,0x3e48bf04,
0x3f71bf62,0x3eacbef1,0xbf463f2c,0x3f22bf3e,0x3f4ebf35,0x3f18bf35,0xbf6d3f5c,0x3ec4bf04,
0x3f78bf7f,0xbe793dc9,0xbe953e16,0x3f75bf7d,0x3f80bf7b,0x3d49be48,0xbf0e3edb,0x3f55bf67,
0xbf183f22,0xbf4e3f46,0x3e95be79,0x3f75bf78,0xbf2c3f35,0xbf3e3f35,0x3ec4beac,0x3f6dbf71,
0xbedb3ef1,0xbf673f62,0x3dc9bd49,0x3f7fbf80,0xbf043f0e,0xbf5c3f55,0x3e48be16,0x3f7bbf7d,
0x3d49be95,0x3f80bf75,0x3f7fbf71,0x3dc9beac,0x3f04bf35,0x3f5cbf35,0x3f6dbf7d,0xbec43e16,
0xbf4e3f22,0x3f18bf46,0x3ef1be79,0x3f62bf78,0xbedb3e48,0x3f67bf7b,0x3f55bf2c,0x3f0ebf3e,
0x3f04bdc9,0xbf5c3f7f,0x3ef1bf4e,0xbf623f18,0xbeac3f35,0xbf713f35,0xbec4bd49,0xbf6d3f80,
0x3f3ebf75,0x3f2cbe95,0x3f46bedb,0x3f22bf67,0x3f7dbf55,0xbe163f0e,0x3f7bbf78,0xbe48be79,
0xbf673ef1,0x3edbbf62,0xbf223d49,0xbf463f80,0x3e16bf35,0x3f7dbf35,0xbf6d3f78,0x3ec43e79,
0x3f043dc9,0xbf5c3f7f,0x3f75bf18,0x3e95bf4e,0xbf2c3f7b,0xbf3e3e48,0x3f0ebf71,0xbf553eac,
0x3f7dbf46,0x3e163f22,0xbf753f5c,0x3e953f04,0x3d493f35,0xbf803f35,0x3ec43edb,0x3f6dbf67,
0xbf713f62,0xbeacbef1,0x3f7fbf3e,0xbdc9bf2c,0xbe79bf0e,0x3f78bf55,0xbe48bf18,0xbf7b3f4e,
0xbf3e3f75,0xbf2cbe95,0xbdc93f67,0x3f7fbedb,0xbe79bf35,0x3f78bf35,0x3f6dbf4e,0xbec4bf18,
0xbe16bf46,0x3f7dbf22,0x3f62bf5c,0xbef1bf04,0x3f71be48,0xbeac3f7b,0xbf55bd49,0xbf0e3f80,
0x3e79bf7f,0x3f78bdc9,0x3f623e16,0x3ef1bf7d,0x3edb3f35,0xbf673f35,0xbec4bf3e,0xbf6d3f2c,
0x3f80be95,0xbd493f75,0x3f22bf71,0xbf46beac,0xbf4e3f55,0xbf18bf0e,0xbf7b3f04,0x3e483f5c,
0x3eac3f62,0xbf713ef1,0x3f46bf3e,0xbf22bf2c,0xbf18bf35,0x3f4ebf35,0xbf6d3f04,0x3ec43f5c,
0xbe793f7f,0xbf78bdc9,0x3e95bf7d,0xbf75be16,0xbd49bf7b,0x3f80be48,0xbf0e3f67,0x3f553edb,
0xbf4ebf22,0x3f18bf46,0xbe95bf78,0xbf753e79,0x3f3e3f35,0xbf2c3f35,0x3ec43f71,0x3f6dbeac,
0xbf67bef1,0x3edbbf62,0xbdc9bf80,0xbf7f3d49,0x3f5c3f0e,0xbf043f55,0x3e483f7d,0x3f7bbe16,
0x3f803e95,0xbd493f75,0xbf7fbeac,0xbdc93f71,0xbf5cbf35,0x3f04bf35,0x3f6dbe16,0xbec4bf7d,
0x3f18bf22,0x3f4e3f46,0xbef1bf78,0xbf623e79,0xbf673e48,0xbedbbf7b,0x3f553f3e,0x3f0ebf2c,
0xbf5c3dc9,0xbf04bf7f,0xbef13f18,0x3f623f4e,0x3f713f35,0xbeac3f35,0xbec4bf80,0xbf6dbd49,
0x3f2c3f75,0xbf3e3e95,0xbf46bf67,0xbf223edb,0x3e16bf55,0x3f7d3f0e,0x3f7b3e79,0xbe48bf78,
0x3edbbef1,0x3f673f62,0x3f223f80,0x3f46bd49,0xbf7dbf35,0x3e16bf35,0xbf6dbe79,0x3ec43f78,
0xbf5cbdc9,0xbf04bf7f,0xbf75bf4e,0xbe953f18,0x3f3e3f7b,0xbf2c3e48,0x3f0ebeac,0xbf55bf71,
0x3e163f46,0xbf7dbf22,0x3f753f04,0xbe95bf5c,0x3f803f35,0x3d493f35,0x3ec43f67,0x3f6d3edb,
0xbeacbf62,0x3f713ef1,0xbf7fbf2c,0x3dc93f3e,0xbf78bf0e,0xbe79bf55,0xbe48bf4e,0xbf7bbf18,
0xbf2cbf75,0x3f3e3e95,0x3dc9bedb,0xbf7fbf67,0xbf78bf35,0xbe79bf35,0x3f6d3f18,0xbec4bf4e,
0x3f7d3f46,0x3e163f22,0xbf62bf04,0x3ef13f5c,0x3eacbe48,0x3f713f7b,0xbf55bf80,0xbf0ebd49,
0x3f783f7f,0xbe793dc9,0xbf62bf7d,0xbef1be16,0x3f673f35,0x3edb3f35,0xbec4bf2c,0xbf6dbf3e,
0xbd493e95,0xbf80bf75,0xbf22beac,0x3f463f71,0x3f183f55,0xbf4ebf0e,0xbf7bbf5c,0x3e483f04,
0xbf71bf62,0xbeacbef1,0xbf46bf2c,0x3f223f3e,0xbf4ebf35,0xbf18bf35,0xbf6dbf5c,0x3ec43f04,
0xbf78bf7f,0x3e793dc9,0xbe95be16,0x3f753f7d,0xbf80bf7b,0xbd49be48,0xbf0ebedb,0x3f553f67,
0x3f803f80,0x3b490000,0x3f803f80,0x3ce23cc9,0x3f803f80,0x3c173bc9,0x3f803f80,0x3d0a3cfb,
0x3f803f80,0x3c7b3c49,0x3f803f80,0x3d233d17,0x3f803f80,0x3cb03c97,0x3f803f80,0x3d3c3d30,
0x3f803f80,0x3c7b0000,0x3f7e3f7e,0x3e0d3dfb,0x3f803f80,0x3d3c3cfb,0x3f7c3f7d,0x3e2c3e1c,
0x3f7f3f80,0x3d9d3d7b,0x3f7b3f7c,0x3e4b3e3b,0x3f7f3f7f,0x3ddb3dbc,0x3f793f7a,0x3e6a3e5a,
0x3f803f80,0x3ce20000,0x3f783f7a,0x3e7c3e60,0x3f7f3f80,0x3da93d62,0x3f743f76,0x3e993e8c,
0x3f7e3f7e,0x3e0d3de2,0x3f703f72,0x3eb43ea7,0x3f7b3f7c,0x3e453e29,0x3f6a3f6d,0x3ece3ec1,
0x3f803f80,0x3d230000,0x3f703f73,0x3eb43ea1,0x3f7e3f7f,0x3df43da3,0x3f683f6c,0x3ed93ec7,
0x3f7b3f7d,0x3e4b3e23,0x3f5e3f63,0x3efe3eec,0x3f763f79,0x3e8d3e73,0x3f543f59,0x3f103f08,
0x3f803f80,0x3d560000,0x3f643f6a,0x3ee83ecf,0x3f7d3f7f,0x3e203dd5,0x3f573f5e,0x3f0b3eff,
0x3f773f7a,0x3e843e54,0x3f473f4f,0x3f213f16,0x3f6f3f74,0x3eb73e9e,0x3f363f3f,0x3f343f2b,
0x3f7f3f80,0x3d840000,0x3f563f5f,0x3f0c3efc,0x3f7b3f7e,0x3e453e04,0x3f423f4d,0x3f273f1a,
0x3f733f78,0x3ea23e82,0x3f2b3f37,0x3f3e3f33,0x3f663f6d,0x3edf3ec1,0x3f113f1f,0x3f533f49,
0x3f7f3f80,0x3d9d0000,0x3f453f51,0x3f233f13,0x3f793f7d,0x3e6a3e1c,0x3f2a3f38,0x3f3f3f32,
0x3f6d3f74,0x3ec03e9b,0x3f0b3f1b,0x3f573f4c,0x3f5c3f65,0x3f033ee3,0x3ed13ef4,0x3f6a3f61,
0x3f7f3f80,0x3db60000,0x3f323f42,0x3f383f27,0x3f773f7c,0x3e873e35,0x3f0f3f21,0x3f543f47,
0x3f673f70,0x3edc3eb2,0x3ece3ef7,0x3f6a3f60,0x3f503f5c,0x3f153f02,0x3e703ea4,0x3f793f73,
0x3f7f3f80,0x3dcf0000,0x3f1d3f31,0x3f4a3f39,0x3f743f7b,0x3e993e4e,0x3ee23f08,0x3f663f59,
0x3f603f6b,0x3ef83eca,0x3e813eb2,0x3f783f70,0x3f423f52,0x3f273f12,0x3d563e1c,0x3f803f7d,
0x3f7e3f80,0x3de80000,0x3f063f1d,0x3f5a3f4a,0x3f713f79,0x3eab3e66,0x3ea23ed8,0x3f733f68,
0x3f583f66,0x3f0a3ee1,0x3dc23e54,0x3f7f3f7a,0x3f333f47,0x3f373f21,0xbe07bc97,0x3f7e3f80,
0x3f7e3f80,0x3e000000,0x3ed93f09,0x3f683f58,0x3f6e3f78,0x3ebd3e7f,0x3e3f3e9e,0x3f7c3f74,
0x3f4f3f60,0x3f173ef7,0xbd843d7b,0x3f7f3f80,0x3f233f3a,0x3f453f2f,0xbe9fbe42,0x3f733f7b,
0x3f7e3f80,0x3e0d0000,0x3ea53ee6,0x3f723f65,0x3f6a3f76,0x3ece3e8c,0x3d563e42,0x3f803f7b,
0x3f453f5a,0x3f233f06,0xbe63bdb0,0x3f7a3f7f,0x3f113f2d,0x3f533f3d,0xbef6beb5,0x3f613f6f,
0x3f7d3f80,0x3e190000,0x3e5d3eb8,0x3f7a3f6f,0x3f663f75,0x3edf3e98,0xbda93d8a,0x3f7f3f7f,
0x3f3b3f53,0x3f2f3f11,0xbec0be6d,0x3f6d3f79,0x3efe3f1f,0x3f5e3f49,0xbf22bf02,0x3f463f5c,
0x3f7d3f80,0x3e260000,0x3ddb3e89,0x3f7f3f77,0x3f623f73,0x3ef03ea4,0xbe5dbd62,0x3f7a3f80,
0x3f303f4c,0x3f3a3f1b,0xbf04bebe,0x3f5b3f6e,0x3ed73f10,0x3f683f54,0xbf43bf26,0x3f253f43,
0x3f7c3f80,0x3e320000,0xbb493e2f,0x3f803f7c,0x3f5e3f71,0x3f003eaf,0xbeb1be35,0x3f703f7c,
0x3f243f44,0x3f443f25,0xbf25bf01,0x3f433f5d,0x3eae3eff,0x3f713f5e,0xbf5ebf45,0x3efe3f24,
0x3f7c3f80,0x3e3f0000,0xbde83d97,0x3f7e3f7f,0x3f593f6e,0x3f083ebb,0xbef0be98,0x3f623f75,
0x3f183f3c,0x3f4e3f2e,0xbf42bf20,0x3f273f48,0x3e843ede,0x3f773f67,0xbf72bf5e,0x3ea83eff,
0x3f7b3f80,0x3e4b0000,0xbe63bcc9,0x3f7a3f80,0x3f543f6c,0x3f103ec7,0xbf15bed2,0x3f503f69,
0x3f0b3f33,0x3f573f37,0xbf5abf3c,0x3f063f2e,0x3e323ebb,0x3f7c3f6e,0xbf7dbf71,0x3e193eaf,
0x3f7a3f80,0x3e570000,0xbea8bdfb,0x3f723f7e,0x3f4e3f69,0x3f183ed2,0xbf30bf05,0x3f3a3f5b,
0x3efb3f2a,0x3f5f3f40,0xbf6dbf53,0x3ec23f11,0x3db63e98,0x3f7f3f75,0xbf80bf7c,0xbd0a3e35,
0x3f7a3f80,0x3e630000,0xbedcbe60,0x3f673f7a,0x3f483f67,0x3f1f3ede,0xbf47bf1f,0x3f213f49,
0x3edf3f20,0x3f663f48,0xbf79bf66,0x3e6a3ee1,0x3b493e66,0x3f803f79,0xbf7abf80,0xbe5d3bc9,
0x3f793f80,0x3e700000,0xbf07bea1,0x3f5a3f73,0x3f423f64,0x3f273ee9,0xbf5bbf36,0x3f043f34,
0x3ec23f16,0x3f6d3f4f,0xbf7fbf74,0x3d903e9b,0xbda93e1c,0x3f7f3f7d,0xbf6cbf7c,0xbec8be29,
0x3f783f80,0x3e7c0000,0xbf1ebecf,0x3f493f6a,0x3f3c3f61,0x3f2e3ef4,0xbf6bbf4b,0x3ecb3f1c,
0x3ea53f0c,0x3f723f57,0xbf7fbf7d,0xbdb63e23,0xbe2c3da3,0x3f7c3f7f,0xbf55bf72,0xbf0ebeaa,
0x3f773f80,0x3e840000,0xbf33befc,0x3f373f5f,0x3f363f5e,0x3f343eff,0xbf77bf5c,0x3e8a3f02,
0x3e873f01,0x3f773f5d,0xbf78bf80,0xbe7c3c49,0xbe813bc9,0x3f783f80,0xbf38bf60,0xbf32befa,
0x3f773f80,0x3e8a0000,0xbf46bf13,0x3f223f51,0x3f2f3f5b,0x3f3b3f05,0xbf7ebf6b,0x3e0d3ecd,
0x3e513eec,0x3f7b3f63,0xbf6bbf7e,0xbecbbe0a,0xbeabbd8a,0x3f713f7f,0xbf14bf47,0xbf51bf21,
0x3f763f80,0x3e900000,0xbf57bf27,0x3f0b3f42,0x3f283f57,0x3f413f0a,0xbf80bf75,0x3b493e92,
0x3e133ed5,0x3f7d3f69,0xbf58bf76,0xbf0abe8f,0xbed4be10,0x3f693f7d,0xbed7bf28,0xbf68bf41,
0x3f753f80,0x3e960000,0xbf65bf39,0x3ee53f31,0x3f213f54,0x3f473f10,0xbf7ebf7c,0xbe073e29,
0x3da93ebe,0x3f7f3f6e,0xbf3fbf69,0xbf2abed5,0xbefbbe5a,0x3f5f3f7a,0xbe7cbf05,0xbf78bf5b,
0x3f743f80,0x3e9c0000,0xbf70bf4a,0x3eb13f1d,0x3f193f50,0x3f4d3f15,0xbf77bf80,0xbe873d30,
0x3cb03ea7,0x3f803f72,0xbf22bf57,0xbf46bf0c,0xbf10be92,0x3f543f75,0xbd84bebb,0xbf7fbf6e,
0x3f733f80,0x3ea20000,0xbf79bf58,0x3e763f09,0x3f113f4d,0x3f533f1a,0xbf6cbf7f,0xbec8bda3,
0xbd233e8f,0x3f803f76,0xbf00bf40,0xbf5ebf2a,0xbf22beb5,0x3f463f6f,0x3df4be4e,0xbf7ebf7b,
0x3f723f80,0x3ea80000,0xbf7ebf65,0x3e073ee6,0x3f0a3f49,0x3f583f1f,0xbf5cbf7b,0xbf03be4e,
0xbdcf3e6d,0x3f7f3f79,0xbeb7bf25,0xbf6fbf44,0xbf32bed8,0x3f383f68,0x3e99bcfb,0xbf74bf80,
0x3f713f80,0x3eae0000,0xbf80bf6f,0x3cb03eb8,0x3f023f45,0x3f5d3f24,0xbf48bf73,0xbf1fbea4,
0xbe263e3b,0x3f7d3f7c,0xbe51bf06,0xbf7bbf5a,0xbf41befa,0x3f283f60,0x3ef03e10,0xbf62bf7d,
0x3f703f80,0x3eb40000,0xbf7fbf77,0xbdb63e89,0x3ef33f41,0x3f613f28,0xbf31bf67,0xbf39bede,
0xbe633e0a,0x3f7a3f7e,0xbd3cbeca,0xbf80bf6b,0xbf4fbf0d,0x3f173f56,0x3f1f3e9e,0xbf48bf74,
0x3f6f3f80,0x3eba0000,0xbf7bbf7c,0xbe4b3e2f,0x3ee23f3d,0x3f663f2d,0xbf17bf57,0xbf4fbf0a,
0xbe903db0,0x3f763f7f,0x3de8be82,0xbf7ebf78,0xbf5bbf1c,0x3f043f4b,0x3f413eef,0xbf28bf63,
0x3f6d3f80,0x3ec00000,0xbf74bf7f,0xbe9c3d97,0x3ed13f38,0x3f6a3f32,0xbef3bf45,0xbf61bf24,
0xbeae3d17,0x3f713f80,0x3e8abde2,0xbf77bf7e,0xbf66bf2b,0x3ee23f3f,0x3f5d3f1c,0xbf02bf4b,
};

struct Maps { CUtensorMap mu, mk, mv, mq, ms, mo; };
typedef const uint32_t* __restrict__ cptr;

#define TSTAMP(i) do {} while (0)
#define STAMP(i) do {} while (0)
#define STAMP_FLUSH() do {} while (0)

__device__ __forceinline__ uint32_t smem_u32(const void* q) { return (uint32_t)__cvta_generic_to_shared(q); }
__device__ __forceinline__ uint32_t mapa(uint32_t a, uint32_t r) { uint32_t o; asm("mapa.shared::cluster.u32 %0,%1,%2;" : "=r"(o) : "r"(a), "r"(r)); return o; }
__device__ __forceinline__ void mbar_init(uint32_t b, uint32_t c) { asm volatile("mbarrier.init.shared::cta.b64 [%0], %1;" ::"r"(b), "r"(c) : "memory"); }
__device__ __forceinline__ void mbar_expect(uint32_t b, uint32_t bytes) { asm volatile("mbarrier.arrive.expect_tx.shared::cta.b64 _, [%0], %1;" ::"r"(b), "r"(bytes) : "memory"); }
__device__ __forceinline__ void mbar_wait(uint32_t b) {
  asm volatile("{.reg .pred p, q; .reg .u32 n;\n"
               "mbarrier.try_wait.parity.shared::cta.b64 p, [%0], 0;\n"
               "@p bra.uni D_%=;\n"
               "mov.u32 n, 0;\n"
               "W_%=: mbarrier.try_wait.parity.shared::cta.b64 p, [%0], 0, 2000;\n"
               "@p bra.uni D_%=;\n"
               "add.u32 n, n, 1; setp.lt.u32 q, n, 262144; @q bra.uni W_%=;\n"
               "trap;\n"
               "D_%=: }" ::"r"(b) : "memory");
}
__device__ __forceinline__ void mbar_wait_lazy(uint32_t b) {
  asm volatile("{.reg .pred p, q; .reg .u32 n; mov.u32 n, 0;\n"
               "W_%=: mbarrier.test_wait.parity.shared::cta.b64 p, [%0], 0;\n"
               "@p bra.uni D_%=;\n"
               "nanosleep.u32 150;\n"
               "add.u32 n, n, 1; setp.lt.u32 q, n, 1048576; @q bra.uni W_%=;\n"
               "trap;\n"
               "D_%=: }" ::"r"(b) : "memory");
}
__device__ __forceinline__ void delay_clks(uint32_t n) {
  uint32_t c0, c1;
  asm volatile("mov.u32 %0, %%clock;" : "=r"(c0));
  do { __nanosleep(40); asm volatile("mov.u32 %0, %%clock;" : "=r"(c1)); } while (c1 - c0 < n);
}
__device__ __forceinline__ void fence_async() { asm volatile("fence.proxy.async.shared::cta;" ::: "memory"); }
__device__ __forceinline__ void fence_async_acq() { asm volatile("fence.proxy.async::generic.acquire.sync_restrict::shared::cluster.cluster;" ::: "memory"); }
__device__ __forceinline__ uint32_t ldg32(const void* q) { uint32_t v; asm volatile("ld.global.nc.u32 %0, [%1];" : "=r"(v) : "l"(q)); return v; }
__device__ __forceinline__ uint32_t ldg32_if(const void* q, int tid) {
  uint32_t v; asm volatile("{.reg .pred p; setp.ge.s32 p, %2, 128; mov.u32 %0, 0; @p ld.global.nc.u32 %0, [%1];}" : "=r"(v) : "l"(q), "r"(tid)); return v;
}
__device__ __forceinline__ void pair_bar(int id) { asm volatile("bar.sync %0, 64;" ::"r"(id) : "memory"); }
__device__ __forceinline__ void wg_bar(int id) { asm volatile("bar.sync %0, 128;" ::"r"(id) : "memory"); }
__device__ __forceinline__ void tma2d(uint32_t dst, const CUtensorMap* m, int c0, int c1, uint32_t bar) {
  asm volatile("cp.async.bulk.tensor.2d.shared::cluster.global.mbarrier::complete_tx::bytes [%0], [%1, {%3, %4}], [%2];" ::"r"(dst), "l"(m), "r"(bar), "r"(c0), "r"(c1) : "memory");
}
__device__ __forceinline__ void tma4d(uint32_t dst, const CUtensorMap* m, int c0, int c2, uint32_t bar) {
  asm volatile("cp.async.bulk.tensor.4d.shared::cluster.global.mbarrier::complete_tx::bytes [%0], [%1, {%3, 0, %4, 0}], [%2];" ::"r"(dst), "l"(m), "r"(bar), "r"(c0), "r"(c2) : "memory");
}
__device__ __forceinline__ void tma5d(uint32_t dst, const CUtensorMap* m, int c0, int c3, uint32_t bar) {
  asm volatile("cp.async.bulk.tensor.5d.shared::cluster.global.mbarrier::complete_tx::bytes [%0], [%1, {%3, 0, 0, %4, 0}], [%2];" ::"r"(dst), "l"(m), "r"(bar), "r"(c0), "r"(c3) : "memory");
}
__device__ __forceinline__ void tma5d_store(const CUtensorMap* m, uint32_t src, int c0, int c3) {
  asm volatile("cp.async.bulk.tensor.5d.global.shared::cta.bulk_group [%0, {%2, 0, 0, %3, 0}], [%1];" ::"l"(m), "r"(src), "r"(c0), "r"(c3) : "memory");
  asm volatile("cp.async.bulk.commit_group;" ::: "memory");
}
__device__ __forceinline__ void ldsm4(uint32_t* r, uint32_t a) { asm volatile("ldmatrix.sync.aligned.m8n8.x4.shared.b16 {%0,%1,%2,%3},[%4];" : "=r"(r[0]), "=r"(r[1]), "=r"(r[2]), "=r"(r[3]) : "r"(a) : "memory"); }
__device__ __forceinline__ void ldsm4t(uint32_t* r, uint32_t a) { asm volatile("ldmatrix.sync.aligned.m8n8.x4.trans.shared.b16 {%0,%1,%2,%3},[%4];" : "=r"(r[0]), "=r"(r[1]), "=r"(r[2]), "=r"(r[3]) : "r"(a) : "memory"); }
__device__ __forceinline__ void ldsm2t(uint32_t* r, uint32_t a) { asm volatile("ldmatrix.sync.aligned.m8n8.x2.trans.shared.b16 {%0,%1},[%2];" : "=r"(r[0]), "=r"(r[1]) : "r"(a) : "memory"); }
__device__ __forceinline__ void stsm4(uint32_t a, uint32_t r0, uint32_t r1, uint32_t r2, uint32_t r3) { asm volatile("stmatrix.sync.aligned.m8n8.x4.shared.b16 [%0],{%1,%2,%3,%4};" ::"r"(a), "r"(r0), "r"(r1), "r"(r2), "r"(r3) : "memory"); }
__device__ __forceinline__ void sts128(uint32_t a, uint32_t r0, uint32_t r1, uint32_t r2, uint32_t r3) { asm volatile("st.shared.v4.u32 [%0],{%1,%2,%3,%4};" ::"r"(a), "r"(r0), "r"(r1), "r"(r2), "r"(r3) : "memory"); }
__device__ __forceinline__ void sts64(uint32_t a, uint32_t r0, uint32_t r1) { asm volatile("st.shared.v2.u32 [%0],{%1,%2};" ::"r"(a), "r"(r0), "r"(r1) : "memory"); }
__device__ __forceinline__ void sts16(uint32_t a, uint32_t r0) { asm volatile("st.shared.u16 [%0],%1;" ::"r"(a), "r"(r0) : "memory"); }
__device__ __forceinline__ void lds128(uint32_t* r, uint32_t a) { asm volatile("ld.shared.v4.u32 {%0,%1,%2,%3},[%4];" : "=r"(r[0]), "=r"(r[1]), "=r"(r[2]), "=r"(r[3]) : "r"(a) : "memory"); }
__device__ __forceinline__ void sts32(uint32_t a, uint32_t r0) { asm volatile("st.shared.u32 [%0],%1;" ::"r"(a), "r"(r0) : "memory"); }
__device__ __forceinline__ uint32_t lds32(uint32_t a) { uint32_t v; asm volatile("ld.shared.u32 %0,[%1];" : "=r"(v) : "r"(a) : "memory"); return v; }
__device__ __forceinline__ uint32_t lds16(uint32_t a) { uint32_t v; asm volatile("ld.shared.u16 %0,[%1];" : "=r"(v) : "r"(a) : "memory"); return v; }
__device__ __forceinline__ uint2 lds64(uint32_t a) { uint2 v; asm volatile("ld.shared.v2.u32 {%0,%1},[%2];" : "=r"(v.x), "=r"(v.y) : "r"(a) : "memory"); return v; }
__device__ __forceinline__ void st_async4(uint32_t a, uint32_t bar, uint32_t r0, uint32_t r1, uint32_t r2, uint32_t r3) {
  asm volatile("st.async.weak.shared::cluster.mbarrier::complete_tx::bytes.v4.b32 [%0],{%1,%2,%3,%4},[%5];" ::"r"(a), "r"(r0), "r"(r1), "r"(r2), "r"(r3), "r"(bar) : "memory");
}
__device__ __forceinline__ void st_async2(uint32_t a, uint32_t bar, uint32_t r0, uint32_t r1) {
  asm volatile("st.async.weak.shared::cluster.mbarrier::complete_tx::bytes.v2.b32 [%0],{%1,%2},[%3];" ::"r"(a), "r"(r0), "r"(r1), "r"(bar) : "memory");
}
__device__ __forceinline__ void arrive_if(uint32_t cond, uint32_t bar) {
  asm volatile("{.reg .pred p; setp.ne.u32 p,%1,0; @p mbarrier.arrive.shared::cta.b64 _, [%0];}" ::"r"(bar), "r"(cond) : "memory");
}
__device__ __forceinline__ uint32_t pk(float lo, float hi) { uint32_t r;
 asm("cvt.rn.bf16x2.f32 %0,%1,%2;" : "=r"(r) : "f"(hi), "f"(lo)); return r; }
__device__ __forceinline__ uint32_t hmul(uint32_t a, uint32_t b) { uint32_t r; asm("mul.rn.bf16x2 %0,%1,%2;" : "=r"(r) : "r"(a), "r"(b)); return r; }
__device__ __forceinline__ uint32_t hfma(uint32_t a, uint32_t b, uint32_t c) { uint32_t r; asm("fma.rn.bf16x2 %0,%1,%2,%3;" : "=r"(r) : "r"(a), "r"(b), "r"(c)); return r; }
__device__ __forceinline__ uint32_t hfnma(uint32_t a, uint32_t b, uint32_t c) { uint32_t r; asm("{.reg .b32 t; mul.bf16x2 t,%1,%2; sub.bf16x2 %0,%3,t;}" : "=r"(r) : "r"(a), "r"(b), "r"(c)); return r; }
__device__ __forceinline__ uint32_t hadd(uint32_t a, uint32_t b) { uint32_t r; asm("add.rn.bf16x2 %0,%1,%2;" : "=r"(r) : "r"(a), "r"(b)); return r; }
__device__ __forceinline__ uint32_t hsub(uint32_t a, uint32_t b) { uint32_t r; asm("sub.rn.bf16x2 %0,%1,%2;" : "=r"(r) : "r"(a), "r"(b)); return r; }
__device__ __forceinline__ uint32_t prmt(uint32_t a, uint32_t b, uint32_t s) { uint32_t r; asm("prmt.b32 %0,%1,%2,%3;" : "=r"(r) : "r"(a), "r"(b), "r"(s)); return r; }
__device__ __forceinline__ float blo(uint32_t w) { return __uint_as_float(w << 16); }
__device__ __forceinline__ float bhi(uint32_t w) { return __uint_as_float(w & 0xffff0000u); }

struct C2 { uint32_t re, im; };
__device__ __forceinline__ C2 cmul2(C2 a, C2 b) { C2 r; r.re = hfnma(a.im, b.im, hmul(a.re, b.re)); r.im = hfma(a.im, b.re, hmul(a.re, b.im)); return r; }
__device__ __forceinline__ C2 cmulc2(C2 a, C2 b) { C2 r; r.re = hfma(a.im, b.im, hmul(a.re, b.re)); r.im = hfnma(a.re, b.im, hmul(a.im, b.re)); return r; }
struct CF { float x, y; };
__device__ __forceinline__ CF cmul(CF a, CF b) { CF r; r.x = fmaf(a.x, b.x, -a.y * b.y); r.y = fmaf(a.x, b.y, a.y * b.x); return r; }
__device__ __forceinline__ CF cmulc(CF a, CF b) { CF r; r.x = fmaf(a.x, b.x, a.y * b.y); r.y = fmaf(a.y, b.x, -a.x * b.y); return r; }
__device__ __forceinline__ CF csq(CF a) {
  CF r; r.x = fmaf(a.x, a.x, -a.y * a.y);
  asm("{.reg .f32 t; mul.ftz.f32 t,%1,%2; mul.ftz.f32 %0,t,0f40000000;}" : "=f"(r.y) : "f"(a.x), "f"(a.y));
  return r;
}
__device__ __forceinline__ CF cexp2i(float lg2, float th) { float m, s, c; asm("ex2.approx.ftz.f32 %0,%1;" : "=f"(m) : "f"(lg2)); __sincosf(th, &s, &c); CF r; r.x = m * c; r.y = m * s; return r; }

__device__ __forceinline__ void wg_fence() { asm volatile("wgmma.fence.sync.aligned;" ::: "memory"); }
__device__ __forceinline__ void wg_commit() { asm volatile("wgmma.commit_group.sync.aligned;" ::: "memory"); }
template <int N> __device__ __forceinline__ void wg_wait() { asm volatile("wgmma.wait_group.sync.aligned %0;" ::"n"(N) : "memory"); }
__device__ __forceinline__ void pin(float* d) {
#pragma unroll
  for (int i = 0; i < 16; i++) asm volatile("" : "+f"(d[i])::"memory");
}
template <int ACC, int TB> __device__ __forceinline__ void wgmma32(float* d, uint32_t a0, uint32_t a1, uint32_t a2, uint32_t a3, uint64_t desc) {
  if (ACC)
    asm volatile("wgmma.mma_async.sync.aligned.m64n32k16.f32.bf16.bf16 {%0,%1,%2,%3,%4,%5,%6,%7,%8,%9,%10,%11,%12,%13,%14,%15}, {%16,%17,%18,%19}, %20, 1, 1, 1, %21;"
                 : "+f"(d[0]), "+f"(d[1]), "+f"(d[2]), "+f"(d[3]), "+f"(d[4]), "+f"(d[5]), "+f"(d[6]), "+f"(d[7]), "+f"(d[8]), "+f"(d[9]), "+f"(d[10]), "+f"(d[11]), "+f"(d[12]), "+f"(d[13]), "+f"(d[14]), "+f"(d[15])
                 : "r"(a0), "r"(a1), "r"(a2), "r"(a3), "l"(desc), "n"(TB) : "memory");
  else
    asm volatile("wgmma.mma_async.sync.aligned.m64n32k16.f32.bf16.bf16 {%0,%1,%2,%3,%4,%5,%6,%7,%8,%9,%10,%11,%12,%13,%14,%15}, {%16,%17,%18,%19}, %20, 0, 1, 1, %21;"
                 : "=f"(d[0]), "=f"(d[1]), "=f"(d[2]), "=f"(d[3]), "=f"(d[4]), "=f"(d[5]), "=f"(d[6]), "=f"(d[7]), "=f"(d[8]), "=f"(d[9]), "=f"(d[10]), "=f"(d[11]), "=f"(d[12]), "=f"(d[13]), "=f"(d[14]), "=f"(d[15])
                 : "r"(a0), "r"(a1), "r"(a2), "r"(a3), "l"(desc), "n"(TB) : "memory");
}
template <int ACC> __device__ __forceinline__ void wgmma64(float* d, uint32_t a0, uint32_t a1, uint32_t a2, uint32_t a3, uint64_t desc) {
  if (ACC)
    asm volatile("wgmma.mma_async.sync.aligned.m64n64k16.f32.bf16.bf16 {%0,%1,%2,%3,%4,%5,%6,%7,%8,%9,%10,%11,%12,%13,%14,%15,%16,%17,%18,%19,%20,%21,%22,%23,%24,%25,%26,%27,%28,%29,%30,%31}, {%32,%33,%34,%35}, %36, 1, 1, 1, 1;"
                 : "+f"(d[0]), "+f"(d[1]), "+f"(d[2]), "+f"(d[3]), "+f"(d[4]), "+f"(d[5]), "+f"(d[6]), "+f"(d[7]), "+f"(d[8]), "+f"(d[9]), "+f"(d[10]), "+f"(d[11]), "+f"(d[12]), "+f"(d[13]), "+f"(d[14]), "+f"(d[15]), "+f"(d[16]), "+f"(d[17]), "+f"(d[18]), "+f"(d[19]), "+f"(d[20]), "+f"(d[21]), "+f"(d[22]), "+f"(d[23]), "+f"(d[24]), "+f"(d[25]), "+f"(d[26]), "+f"(d[27]), "+f"(d[28]), "+f"(d[29]), "+f"(d[30]), "+f"(d[31])
                 : "r"(a0), "r"(a1), "r"(a2), "r"(a3), "l"(desc) : "memory");
  else
    asm volatile("wgmma.mma_async.sync.aligned.m64n64k16.f32.bf16.bf16 {%0,%1,%2,%3,%4,%5,%6,%7,%8,%9,%10,%11,%12,%13,%14,%15,%16,%17,%18,%19,%20,%21,%22,%23,%24,%25,%26,%27,%28,%29,%30,%31}, {%32,%33,%34,%35}, %36, 0, 1, 1, 1;"
                 : "=f"(d[0]), "=f"(d[1]), "=f"(d[2]), "=f"(d[3]), "=f"(d[4]), "=f"(d[5]), "=f"(d[6]), "=f"(d[7]), "=f"(d[8]), "=f"(d[9]), "=f"(d[10]), "=f"(d[11]), "=f"(d[12]), "=f"(d[13]), "=f"(d[14]), "=f"(d[15]), "=f"(d[16]), "=f"(d[17]), "=f"(d[18]), "=f"(d[19]), "=f"(d[20]), "=f"(d[21]), "=f"(d[22]), "=f"(d[23]), "=f"(d[24]), "=f"(d[25]), "=f"(d[26]), "=f"(d[27]), "=f"(d[28]), "=f"(d[29]), "=f"(d[30]), "=f"(d[31])
                 : "r"(a0), "r"(a1), "r"(a2), "r"(a3), "l"(desc) : "memory");
}
__device__ __forceinline__ void mma16816z(float* d, uint32_t a0, uint32_t a1, uint32_t a2, uint32_t a3, uint32_t b0, uint32_t b1) {
  asm("mma.sync.aligned.m16n8k16.row.col.f32.bf16.bf16.f32 {%0,%1,%2,%3},{%4,%5,%6,%7},{%8,%9},{%10,%10,%10,%10};"
      : "=f"(d[0]), "=f"(d[1]), "=f"(d[2]), "=f"(d[3]) : "r"(a0), "r"(a1), "r"(a2), "r"(a3), "r"(b0), "r"(b1), "f"(0.f));
}
__device__ __forceinline__ void mma16816(float* d, uint32_t a0, uint32_t a1, uint32_t a2, uint32_t a3, uint32_t b0, uint32_t b1) {
  asm("mma.sync.aligned.m16n8k16.row.col.f32.bf16.bf16.f32 {%0,%1,%2,%3},{%4,%5,%6,%7},{%8,%9},{%0,%1,%2,%3};"
               : "+f"(d[0]), "+f"(d[1]), "+f"(d[2]), "+f"(d[3]) : "r"(a0), "r"(a1), "r"(a2), "r"(a3), "r"(b0), "r"(b1));
}
constexpr uint64_t D_SEQ = ((uint64_t)(1024 >> 4) << 16) | ((uint64_t)(256 >> 4) << 32) | (3ull << 62);
constexpr uint64_t D_XT = ((uint64_t)(2048 >> 4) << 16) | ((uint64_t)(512 >> 4) << 32) | (2ull << 62);
constexpr uint64_t D_F2 = ((uint64_t)(128 >> 4) << 16) | ((uint64_t)(256 >> 4) << 32);

struct Consts { uint32_t f1[8]; C2 tw[2]; };

__device__ __forceinline__ void load_consts(Consts& k, const uint4* ct) {
  const uint4 c0 = __ldg(ct), c1 = __ldg(ct + 128), c2 = __ldg(ct + 256);
  k.f1[0] = c0.x; k.f1[1] = c0.y; k.f1[2] = c0.z; k.f1[3] = c0.w; k.f1[4] = c1.x; k.f1[5] = c1.y; k.f1[6] = c1.z; k.f1[7] = c1.w;
  k.tw[0].re = c2.x; k.tw[0].im = c2.y; k.tw[1].re = c2.z; k.tw[1].im = c2.w;
}

template <int KSTEP> __device__ __forceinline__ void issue_s1(float* d, const Consts& k, uint64_t lo) {
  wg_fence();
  wgmma64<0>(d, k.f1[0], k.f1[1], k.f1[2], k.f1[3], lo);
  wgmma64<1>(d, k.f1[4], k.f1[5], k.f1[6], k.f1[7], lo + (KSTEP >> 4));
  wg_commit();
}
template <bool FENCE = true> __device__ __forceinline__ void issue_s2(float* d, const C2 (&x)[2][2], uint64_t lo) {
  if (FENCE) wg_fence();
  wgmma32<0, 0>(d, x[0][0].re, x[1][0].re, x[0][1].re, x[1][1].re, lo);
  wgmma32<1, 0>(d, x[0][0].im, x[1][0].im, x[0][1].im, x[1][1].im, lo + (1024 >> 4));
  wg_commit();
}
__device__ __forceinline__ void issue_last(float* d, uint32_t la, uint64_t lb) {
  uint32_t a[4][4];
#pragma unroll
  for (int s = 0; s < 4; s++) ldsm4t(a[s], la + 256 * s);
  wg_fence();
  wgmma32<0, 0>(d, a[0][0], a[0][1], a[0][2], a[0][3], lb);
  wgmma32<1, 0>(d, a[1][0], a[1][1], a[1][2], a[1][3], lb + (1024 >> 4));
  wgmma32<1, 0>(d, a[2][0], a[2][1], a[2][2], a[2][3], lb + (2048 >> 4));
  wgmma32<1, 0>(d, a[3][0], a[3][1], a[3][2], a[3][3], lb + (3072 >> 4));
  wg_commit();
}
template <int BS> __device__ __forceinline__ void post_s1(C2 (&x)[2][2], const float* d, const C2 (&tw)[2]) {
#pragma unroll
  for (int i = 0; i < 4; i++) {
    const float* e = d + BS * (i >> 1) + 4 * (i & 1);
    C2 t; t.re = pk(e[0], e[1]); t.im = pk(e[2], e[3]);
    x[i >> 1][i & 1] = cmul2(t, tw[i & 1]);
  }
}
__device__ __forceinline__ void post_s2(C2 (&x)[2][2], float* d) {
  pin(d);
#pragma unroll
  for (int t = 0; t < 2; t++) {
    x[0][t].re = pk(d[4 * t], d[4 * t + 1]);         x[1][t].re = pk(d[4 * t + 2], d[4 * t + 3]);
    x[0][t].im = pk(d[8 + 4 * t], d[9 + 4 * t]);     x[1][t].im = pk(d[10 + 4 * t], d[11 + 4 * t]);
  }
}

struct KState { C2 k0[2], k1[2], p2[2], p3[2]; };

template <int H> __device__ __forceinline__ void pointwise(C2 (&x)[2][2], KState& s) {
#pragma unroll
  for (int t = 0; t < 2; t++) {
    const C2 u0 = x[0][t], u1 = x[1][t], k0 = s.k0[t], k1 = s.k1[t], p2 = s.p2[t], p3 = s.p3[t];
    C2 q0, q1;
    if (H == 0) {
      q1.re = hmul(u1.re, k0.re); q1.im = hmul(u1.re, k0.im);
      q0.re = hmul(u0.re, k0.re); q0.im = hmul(u0.re, k0.im);
    } else {
      q1.re = hfma(u1.re, k0.re, p3.re); q1.im = hfma(u1.re, k0.im, p3.im);
      q0.re = hfma(u0.re, k0.re, p2.re); q0.im = hfma(u0.re, k0.im, p2.im);
    }
    q1.re = hfma(u0.re, k1.re, q1.re);  q1.im = hfma(u0.re, k1.im, q1.im);
    q0.re = hfnma(u0.im, k0.im, q0.re); q0.im = hfma(u0.im, k0.re, q0.im);
    q1.re = hfnma(u0.im, k1.im, q1.re); q1.im = hfma(u0.im, k1.re, q1.im);
    q1.re = hfnma(u1.im, k0.im, q1.re); q1.im = hfma(u1.im, k0.re, q1.im);
    x[0][t] = q0; x[1][t] = q1;
    if (H == 0) {
      C2 n2, n3;
      n2.re = hmul(u1.re, k1.re);         n2.im = hmul(u1.re, k1.im);        n3.re = hmul(u1.re, p2.re);         n3.im = hmul(u1.re, p2.im);
      n2.re = hfnma(u1.im, k1.im, n2.re); n2.im = hfma(u1.im, k1.re, n2.im); n3.re = hfnma(u1.im, p2.im, n3.re); n3.im = hfma(u1.im, p2.re, n3.im);
      n2.re = hfma(u0.re, p2.re, n2.re);  n2.im = hfma(u0.re, p2.im, n2.im); n3.re = hfma(u0.re, p3.re, n3.re);  n3.im = hfma(u0.re, p3.im, n3.im);
      n2.re = hfnma(u0.im, p2.im, n2.re); n2.im = hfma(u0.im, p2.re, n2.im); n3.re = hfnma(u0.im, p3.im, n3.re); n3.im = hfma(u0.im, p3.re, n3.im);
      s.p2[t] = n2; s.p3[t] = n3;
    }
  }
}

#define TS(i) do {} while (0)
__device__ __forceinline__ void post_s3(float* d, const C2 (&tw)[2], uint32_t sa) {
  C2 x[2][2];
  post_s2(x, d);
#pragma unroll
  for (int i = 0; i < 4; i++) x[i >> 1][i & 1] = cmulc2(x[i >> 1][i & 1], tw[i & 1]);
  stsm4(sa, x[0][0].re, x[0][1].re, x[1][0].re, x[1][1].re);
  stsm4(sa + 128, x[0][0].im, x[0][1].im, x[1][0].im, x[1][1].im);
}
__device__ __forceinline__ void make_kt(KState& s, const C2 (&a)[2][2], const C2 (&b)[2][2], uint32_t dd) {
#pragma unroll
  for (int t = 0; t < 2; t++) {
    s.k0[t].re = hadd(a[0][t].re, dd);           s.k0[t].im = a[0][t].im;
    s.k1[t].re = hadd(a[1][t].re, a[0][t].im);   s.k1[t].im = hsub(a[1][t].im, a[0][t].re);
    s.p2[t].re = hadd(b[0][t].re, a[1][t].im);   s.p2[t].im = hsub(b[0][t].im, a[1][t].re);
    s.p3[t].re = hadd(b[1][t].re, b[0][t].im);   s.p3[t].im = hsub(b[1][t].im, b[0][t].re);
  }
}
__device__ __forceinline__ void put_y(float* d, const uint32_t (&ya)[4], const uint32_t (&yb)[4]) {
  pin(d);
#pragma unroll
  for (int i = 0; i < 4; i++)
    st_async2(ya[i], yb[i], pk(d[4 * i], d[4 * i + 1]), pk(d[4 * i + 2], d[4 * i + 3]));
}
__device__ __forceinline__ void next_y(uint32_t (&ya)[4], uint32_t (&yb)[4], uint32_t da) {
#pragma unroll
  for (int i = 0; i < 4; i++) { ya[i] += da; yb[i] += 24; }
}

__device__ __forceinline__ void conv_pair(const Consts& k, uint32_t kb, uint32_t xt, uint32_t f2, uint32_t xbar, uint32_t ybar, uint32_t dd0, uint32_t dd1,
                                          uint32_t (&ya)[4], uint32_t (&yb)[4], uint32_t sa, uint32_t la, int bar
) {
  float D[32], Z[16];
  KState ka = {}, kbs = {};
  const uint64_t ks = kb | D_SEQ, xs = xt | D_XT, ff = f2 | D_F2, fi = ff + 128, fl = ff + 256;
  issue_s1<512>(D, k, ks);
#pragma unroll
  for (int st = 0; st < 4; st++) {
    float X[16], Y[16];
    C2 x[2][2], y[2][2];
    if (st == 3) mbar_wait(ybar);
    wg_wait<0>();
    if (st == 3) { put_y(Z, ya, yb); next_y(ya, yb, 12288); }
    pin(D); pin(D + 16);
    if (st < 2) { post_s1<8>(x, D, k.tw); post_s1<8>(y, D + 16, k.tw); }
    else { post_s1<16>(x, D, k.tw); post_s1<16>(y, D + 8, k.tw); }
    issue_s2(X, x, ff); issue_s2<false>(Y, y, ff);
    wg_wait<1>(); post_s2(x, X);
    if (st < 2) {
      wg_wait<0>(); post_s2(y, Y);
      if (st == 0) { issue_s1<512>(D, k, ks + 256); make_kt(ka, x, y, dd0); }
      else { STAMP(s0); mbar_wait(xbar); fence_async_acq(); STAMP(s0 + 1); issue_s1<1024>(D, k, xs); make_kt(kbs, x, y, dd1); }
    } else {
      if (st == 2) pointwise<0>(x, ka); else pointwise<1>(x, ka);
      issue_s2(X, x, fi);
      wg_wait<1>(); post_s2(y, Y);
      if (st == 2) pointwise<0>(y, kbs); else pointwise<1>(y, kbs);
      issue_s2(Y, y, fi);
      wg_bar(bar);
      wg_wait<1>(); post_s3(X, k.tw, sa);
      wg_wait<0>(); post_s3(Y, k.tw, sa + 4096);
      if (st == 2) { STAMP(s0 + 2); mbar_wait(xbar + 8); fence_async_acq(); STAMP(s0 + 3); issue_s1<1024>(D, k, xs + 256); }
      wg_bar(bar);
      issue_last(Z, la, fl);
    }
  }
  wg_wait<0>(); put_y(Z, ya, yb);
}

struct Anchors { CF w1, w2, w4, w6, w8, w16, w32, w64, w128, w256, w512, w1024, c; };
__device__ __forceinline__ void gen_anchors(Anchors& o, float are, float aim, float bre, float bim, float cre, float cim, float dt) {
  const float ar = are * (dt * 1.4426950408889634f), th = aim * dt;
  o.w1 = cexp2i(ar, th); o.w64 = cexp2i(64.f * ar, 64.f * th);
  o.w2 = csq(o.w1); o.w4 = csq(o.w2); o.w6 = cmul(o.w4, o.w2); o.w8 = csq(o.w4); o.w16 = csq(o.w8); o.w32 = csq(o.w16);
  o.w128 = csq(o.w64); o.w256 = csq(o.w128); o.w512 = csq(o.w256); o.w1024 = csq(o.w512);
  const float br = bre * dt, bi = bim * dt;
  o.c.x = fmaf(br, cre, -bi * cim); o.c.y = fmaf(-br, cim, -bi * cre);
}
__device__ __forceinline__ C2 pk2(CF a, CF b) { C2 r; r.re = pk(a.x, b.x); r.im = pk(a.y, b.y); return r; }
template <int PL, int H> __device__ __forceinline__ void put_row(uint32_t ta, C2 v) {
  sts32((ta ^ (16 * H)) + 128 * H + 2048 * PL, v.re);
  sts32((ta ^ (16 * H)) + 128 * H + 2048 * PL + 1024, v.im);
}
__device__ __forceinline__ void gen_tables(const Anchors& a, const Anchors& b, uint32_t ta, uint32_t va) {
  const C2 w8 = pk2(a.w8, b.w8), w16 = pk2(a.w16, b.w16), w32 = pk2(a.w32, b.w32), w24 = cmul2(w8, w16);
  const C2 one = {0x3f803f80u, 0u};
  put_row<0, 0>(ta, one); put_row<0, 1>(ta, w8); put_row<0, 2>(ta, w16); put_row<0, 3>(ta, w24); put_row<0, 4>(ta, w32);
  put_row<0, 5>(ta, cmul2(w8, w32)); put_row<0, 6>(ta, cmul2(w16, w32)); put_row<0, 7>(ta, cmul2(w24, w32));
  const C2 v1 = pk2(a.w64, b.w64), v2 = pk2(a.w128, b.w128);
  sts128(va, v1.re, v1.im, v2.re, v2.im);
  const C2 w1 = pk2(a.w1, b.w1), c = pk2(a.c, b.c);
  const C2 h2 = cmulc2(c, pk2(a.w2, b.w2)), h4 = cmulc2(c, pk2(a.w4, b.w4)), h6 = cmulc2(c, pk2(a.w6, b.w6));
  put_row<1, 0>(ta, c);  put_row<1, 1>(ta, cmulc2(c, w1));  put_row<1, 2>(ta, h2); put_row<1, 3>(ta, cmulc2(h2, w1));
  put_row<1, 4>(ta, h4); put_row<1, 5>(ta, cmulc2(h4, w1)); put_row<1, 6>(ta, h6); put_row<1, 7>(ta, cmulc2(h6, w1));
  const C2 w256 = pk2(a.w256, b.w256), w512 = pk2(a.w512, b.w512), w1024 = pk2(a.w1024, b.w1024);
  const C2 g0 = cmulc2(c, w256), g2 = cmulc2(h4, w256), g4 = cmulc2(c, w512), g6 = cmulc2(g0, w512), f0 = cmulc2(c, w1024);
  put_row<2, 0>(ta, g0); put_row<2, 1>(ta, cmulc2(h2, w256)); put_row<2, 2>(ta, g2); put_row<2, 3>(ta, cmulc2(h6, w256));
  put_row<2, 4>(ta, g4); put_row<2, 5>(ta, cmulc2(h4, w512)); put_row<2, 6>(ta, g6); put_row<2, 7>(ta, cmulc2(g2, w512));
  put_row<3, 0>(ta, f0); put_row<3, 1>(ta, cmulc2(g0, w1024)); put_row<3, 2>(ta, cmulc2(g4, w1024)); put_row<3, 3>(ta, cmulc2(g6, w1024));
  put_row<3, 4>(ta, cmulc2(f0, w1024));
}
__device__ __forceinline__ void gen_mma(float (&acc)[2][3][4], uint32_t la, uint32_t va) {
#pragma unroll
  for (int s = 0; s < 8; s++) {
    uint32_t a[4], d[4], v[4];
    ldsm4(a, la ^ (16 * s));
    lds128(v, va + 64 * s);
    ldsm4(d, (la ^ (16 * s)) + 4096);
    const C2 u = {hadd(a[0], 0u), hadd(a[1], 0u)}, v1 = {v[0], v[1]}, v2 = {v[2], v[3]};
    const C2 l1 = cmul2(u, v1), l2 = cmul2(u, v2), l3 = cmul2(l1, v2);
    if (s == 0) {
      mma16816z(acc[0][0], u.re, l1.re, u.im, l1.im, a[2], a[3]);
      mma16816z(acc[0][1], u.re, l1.re, u.im, l1.im, d[0], d[1]);
      mma16816z(acc[0][2], u.re, l1.re, u.im, l1.im, d[2], d[3]);
      mma16816z(acc[1][0], l2.re, l3.re, l2.im, l3.im, a[2], a[3]);
      mma16816z(acc[1][1], l2.re, l3.re, l2.im, l3.im, d[0], d[1]);
      mma16816z(acc[1][2], l2.re, l3.re, l2.im, l3.im, d[2], d[3]);
    } else {
      mma16816(acc[0][0], u.re, l1.re, u.im, l1.im, a[2], a[3]);
      mma16816(acc[0][1], u.re, l1.re, u.im, l1.im, d[0], d[1]);
      mma16816(acc[0][2], u.re, l1.re, u.im, l1.im, d[2], d[3]);
      mma16816(acc[1][0], l2.re, l3.re, l2.im, l3.im, a[2], a[3]);
      mma16816(acc[1][1], l2.re, l3.re, l2.im, l3.im, d[0], d[1]);
      mma16816(acc[1][2], l2.re, l3.re, l2.im, l3.im, d[2], d[3]);
    }
  }
}
__device__ __forceinline__ uint32_t scratch_of(int ww) { return (ww < 9 ? OFF_RK2 : OFF_XT + 24576 - 9 * 8192) + 8192 * ww; }
__device__ __forceinline__ uint32_t swz128(uint32_t lin) { return lin ^ (((lin >> 7) & 7) << 4); }

#define PROF_PARAMS
#define PROF_ARGS
struct GenAddr { uint32_t ta, va, la, lv, e1, e2, k0, c1, c1b, c2, g0, g1, d0, d1, d2; int dp; };
__device__ __forceinline__ void gen_addr(GenAddr& a, uint32_t sb, int wg, int warp, int lane) {
  const int rho = lane >> 2, q = lane & 3, kc = warp >> 1, kh = warp & 1, j = 16 * kh + rho, i = 32 * kh + lane;
  const uint32_t tb = sb + scratch_of(4 * wg + warp), tp = sb + scratch_of(4 * wg + (warp ^ 1)), vb = sb + OFF_KB + 8192 * wg + 512 * warp;
  const uint32_t kd = sb + OFF_KB + 8192 * wg + 4096 * kc, ct = (kh ? tp : tb) + 1024;
  a.ta = tb + 4 * lane; a.va = vb + 16 * lane; a.la = tb + 1024 * (lane >> 3) + 144 * (lane & 7); a.lv = vb + 16 * q;
  a.e1 = tb + 16 * lane; a.e2 = tb + 512 + 8 * lane; a.dp = tp - tb;
  a.k0 = kd + swz128(16 * j) + 4 * q;
  a.c1 = ct + (q < 2 ? 8 * j + 4 * q : 4 * j + 128 * q); a.c1b = a.c1 + (q < 2 ? 64 : 32); a.c2 = ct + 512 + 128 * q + 2 * j;
  a.g0 = ct + 8 * lane; a.g1 = ct + 4 * i;
  a.d0 = kd + swz128(16 * lane + 512); a.d1 = kd + 1024 + swz128(16 * i); a.d2 = kd + 2048 + swz128(32 * i);
  asm volatile("" : "+r"(a.ta), "+r"(a.va), "+r"(a.la), "+r"(a.lv), "+r"(a.e1), "+r"(a.e2), "+r"(a.k0), "+r"(a.c1), "+r"(a.c1b), "+r"(a.c2), "+r"(a.g0), "+r"(a.g1),
               "+r"(a.d0), "+r"(a.d1), "+r"(a.d2));
}
__device__ __forceinline__ void gen_kernels(const GenAddr& ad, uint32_t sb, int wg, int warp, int lane, uint32_t w_are, uint32_t w_aim, uint32_t w_bre, uint32_t w_bim,
                                            uint32_t w_cre, uint32_t w_cim, uint32_t w_ldt, Consts& k, const uint4* ctab PROF_PARAMS) {
  const int q = lane & 3, kc = warp >> 1, kh = warp & 1;
  const float dt = __bfloat162float(__float2bfloat16_rn(expf(kc ? bhi(w_ldt) : blo(w_ldt))));
  float acc[2][3][4];
  {
    Anchors a, b;
    gen_anchors(a, blo(w_are), blo(w_aim), blo(w_bre), blo(w_bim), blo(w_cre), blo(w_cim), dt);
    gen_anchors(b, bhi(w_are), bhi(w_aim), bhi(w_bre), bhi(w_bim), bhi(w_cre), bhi(w_cim), dt);
    gen_tables(a, b, ad.ta, ad.va);
  }
  asm volatile("barrier.cluster.wait.acquire.aligned;" ::: "memory");
  load_consts(k, ctab);
  arrive_if(warp == 0 && lane == 0, sb + OFF_BAR + 8 * B_P1);
  __syncwarp();
  STAMP(1);
  gen_mma(acc, ad.la, ad.lv);
  __syncwarp();
  STAMP(2);
  uint32_t w[6];
  {
    uint32_t give[6];
#pragma unroll
    for (int n = 0; n < 6; n++) {
      const uint32_t p0 = pk(acc[0][n >> 1][2 * (n & 1)], acc[0][n >> 1][2 * (n & 1) + 1]), p1 = pk(acc[1][n >> 1][2 * (n & 1)], acc[1][n >> 1][2 * (n & 1) + 1]);
      w[n] = kh ? p1 : p0; give[n] = kh ? p0 : p1;
    }
    sts128(ad.e1, give[0], give[1], give[2], give[3]);
    sts64(ad.e2, give[4], give[5]);
  }
  wg_bar(1 + wg);
  {
    uint32_t o[4];
    lds128(o, ad.e1 + ad.dp);
    const uint2 o2 = lds64(ad.e2 + ad.dp);
    w[0] = hadd(w[0], o[0]); w[1] = hadd(w[1], o[1]); w[2] = hadd(w[2], o[2]); w[3] = hadd(w[3], o[3]); w[4] = hadd(w[4], o2.x); w[5] = hadd(w[5], o2.y);
    sts32(ad.k0, w[0]); sts32((ad.k0 ^ 16) + 128, w[1]);
    sts32(ad.c1, w[2]); sts32(ad.c1b, w[3]);
    if (q < 3) { sts16(ad.c2, w[4]); sts16(ad.c2 + 16, w[5]); }
    if (q < 2) { sts16(ad.c2 + 64, w[4] >> 16); sts16(ad.c2 + 80, w[5] >> 16); }
  }
  pair_bar(5 + 2 * wg + kc);
  STAMP(9);
  {
    const uint32_t b01 = lds32(ad.g1 + 256), b2 = lds16(ad.g1 + 260), c01 = lds32(ad.g1 + 512), c2 = lds16(ad.g1 + 516);
    if (kh == 0) {
      const uint2 a = lds64(ad.g0);
      const uint32_t a4 = lds16(ad.g0 + 8);
      sts128(ad.d0, prmt(a.x, 0, 0x1010), prmt(a.x, a.y, 0x5432), prmt(a.y, 0, 0x1010), prmt(a.y, a4, 0x5432));
    }
    sts128(ad.d1, prmt(b01, 0, 0x1010), b01, prmt(b01, 0, 0x3232), prmt(b2, 0, 0x1010));
    sts128(ad.d2, prmt(c01, 0, 0x1010), prmt(c01, 1, 0x1010), c01, prmt(c01, 0, 0x3232));
    sts128(ad.d2 ^ 16, prmt(c01, 1, 0x3232), prmt(c01, 2, 0x3232), prmt(c2, 0, 0x1010), prmt(c2, 1, 0x1010));
  }
}

__global__ void __cluster_dims__(3, 1, 1) __launch_bounds__(NTHREADS, 1)
s4h3_kernel(cptr g_are, int o_aim, int o_bre, int o_bim, int o_cre, int o_cim, int o_ldt, uint32_t zero,
            const uint4* __restrict__ g_ctab, cptr g_dskip, cptr g_ssmd, cptr g_shiftk, cptr g_f2tab,
            const __grid_constant__ Maps p) {
  extern __shared__ __align__(1024) uint8_t smem[];
  const int tid = threadIdx.x, lane = tid & 31, t128 = tid & 127;
  uint32_t rank; asm("mov.u32 %0, %%cluster_ctarank;" : "=r"(rank));
  const int ch0 = (blockIdx.x / 3) * 16;
  cptr g_aim = g_are + (int64_t)o_aim * 64, g_bre = g_are + (int64_t)o_bre * 64, g_bim = g_are + (int64_t)o_bim * 64, g_cre = g_are + (int64_t)o_cre * 64;
  cptr g_cim = g_are + (int64_t)o_cim * 64, g_logdt = g_are + (int64_t)o_ldt * 64;
  uint32_t w_are, w_aim, w_ldt, w_bre, w_bim, w_cre, w_cim;
  {
    const int s9 = 3 * (int)rank + min(3 - (tid >> 7), 2), sl = s9 == 8 ? 5 : s9, mo = (ch0 + 2 * sl) * (NMODE / 2) + t128;
    w_are = ldg32_if(g_are + mo, tid); w_aim = ldg32_if(g_aim + mo, tid); w_ldt = ldg32_if(g_logdt + (ch0 >> 1) + sl, tid);
    w_bre = ldg32_if(g_bre + mo, tid); w_bim = ldg32_if(g_bim + mo, tid); w_cre = ldg32_if(g_cre + mo, tid); w_cim = ldg32_if(g_cim + mo, tid);
  }
  const int wg = __shfl_sync(0xffffffffu, tid >= 128 ? 3 - (tid >> 7) : -1, 0), warp = __shfl_sync(0xffffffffu, (tid >> 5) & 3, 0);
  const uint32_t sb = smem_u32(smem);
  const uint32_t bars = sb + OFF_BAR;
  STAMP(23);
  const int nchunk = rank == 1 ? 2 : 3;
  const int cbase = 2 * rank + (rank != 0);

  if (__builtin_expect(wg < 0, 1)) {
    asm volatile("setmaxnreg.dec.sync.aligned.u32 80;");
    if (lane == 0) {
      const uint32_t b0 = bars + 96 * warp;
#pragma unroll
      for (int i = 0; i < 12; i++) mbar_init(b0 + 8 * i, i == 10 && warp == 1 ? 10 : 1);
      if (warp == 3) mbar_init(bars + 8 * B_P1, rank == 1 ? 2 : 3);
      asm volatile("fence.mbarrier_init.release.cluster;" ::: "memory");
    }
    __syncwarp();
    asm volatile("barrier.cluster.arrive.relaxed.aligned;" ::: "memory");
    if (t128 == 0) {
      delay_clks(PDELAY);
#pragma unroll
      for (int i = 0; i < 6; i++) {
        const int hf = i >= 3, j = i - 3 * hf;
        if (j < 2 || rank != 1) tma4d(sb + OFF_RU + 4096 * i, &p.mu, ch0, 16 * (8 * hf + cbase + j), bars + 8 * (B_U + i));
      }
    }
    if (lane == 0) {
      const uint32_t b0 = bars + 96 * warp, t1 = warp == 0 ? 4352 + 4096 : warp == 1 ? 8192 : 4096, t2 = warp == 1 ? 0 : t1;
#pragma unroll
      for (int i = 0; i < 12; i++) {
        uint32_t tx = (i < 6 ? 4096 : i == 10 ? t2 : t1) + (i == 9 && warp == 1 ? 64 : 0);
        mbar_expect(b0 + 8 * i, tx);
      }
    }
    __syncwarp();
    if (warp == 0) {
      STAMP(0);
      asm volatile("barrier.cluster.wait.acquire.aligned;" ::: "memory");
      STAMP(1);
      if (lane == 0) {
        asm volatile("cp.async.bulk.shared::cluster.global.mbarrier::complete_tx::bytes [%0], [%1], 8192, [%2];" ::"r"(sb + OFF_F2), "l"(g_f2tab), "r"(bars + 8 * B_F) : "memory");
        asm volatile("cp.async.bulk.shared::cluster.global.mbarrier::complete_tx::bytes [%0], [%1], 32, [%2];" ::"r"(sb + OFF_D), "l"(g_dskip + (ch0 >> 1)), "r"(bars + 8 * B_F) : "memory");
        asm volatile("cp.async.bulk.shared::cluster.global.mbarrier::complete_tx::bytes [%0], [%1], 32, [%2];" ::"r"(sb + OFF_D + 32), "l"(g_ssmd + (ch0 >> 1)), "r"(bars + 8 * B_F) : "memory");
        mbar_wait_lazy(bars + 8 * (B_U + G1));
#pragma unroll 1
        for (int w = 2; w >= 0; w--) {
          const int sl = 3 * rank + w;
          if (sl != 2) tma2d(sb + OFF_KB + 24576 + 8192 * w, &p.ms, 0, (ch0 + 2 * (sl < 2 ? sl : sl - 1)) * 32, bars + 8 * (B_S + w));
        }
#pragma unroll 1
        for (int i = 0; i < 6; i++) {
          const int hf = i >= 3, j = i - 3 * hf;
          if (i == 3) {
            STAMP(2); mbar_wait_lazy(bars + 8 * B_KG); fence_async();
          }
          if (j < nchunk) {
            tma4d(sb + OFF_RK1 + (OFF_RK2 - OFF_RK1) * hf + 4352 * j, &p.mk, ch0, 16 * (8 * hf + cbase + j) - 1, bars + 8 * (B_KV + i));
            tma4d(sb + OFF_RV1 + (OFF_RV2 - OFF_RV1) * hf + 4096 * j, &p.mv, ch0, 16 * (8 * hf + cbase + j), bars + 8 * (B_KV + i));
          }
        }
        STAMP(3);
#pragma unroll 1
        for (int i = 0; i < 6; i++) {
          const int hf = i >= 3, j = i - 3 * hf;
          if (j < nchunk) tma5d(sb + OFF_RQ + 4096 * i, &p.mq, ch0, 4 * (8 * hf + cbase + j), bars + 8 * (B_Q + i));
        }
        STAMP(4);
      }
    } else {
      const int j = warp - 1;
      const int cl = lane >> 2;
      uint32_t sh[2][2];
#pragma unroll
      for (int hc = 0; hc < 2; hc++) { sh[hc][0] = ldg32(g_shiftk + 2 * (ch0 + 8 * hc + cl)); sh[hc][1] = ldg32(g_shiftk + 2 * (ch0 + 8 * hc + cl) + 1); }
      const int rs = 32 * (lane >> 3) + (lane & 7), r1 = rs + 2 * (lane >> 3) + 2, r2 = 34 * (2 + ((lane >> 3) & 1)) + (lane & 7);
      const uint32_t ro = sb + 4096 * j + 32 * rs + 16 * ((rs >> 2) & 1), ro1 = sb + 4352 * j + 32 * r1 + 16 * ((r1 >> 2) & 1), ro2 = sb + 4352 * j + 32 * r2 + 16 * ((r2 >> 2) & 1);
      const uint32_t cg = cbase + j, r4 = cg & 3;
      const uint32_t xo = 512 * cg + 64 * (((lane >> 1) & 1) ^ r4) + ((32 * (cl & 1) + 16 * (lane & 1)) ^ ((r4 >> 1) << 4));
      asm volatile("barrier.cluster.wait.acquire.aligned;" ::: "memory");
      if (j < nchunk) {
        uint32_t da[2], bd[2];
#pragma unroll
        for (int hc = 0; hc < 2; hc++) {
          const uint32_t sl = 4 * hc + (cl >> 1), dr = (sl * 11) >> 5, dw = sl - 3 * dr, db = mapa(sb, dr);
          da[hc] = db + OFF_XT + 8192 * dw + xo; bd[hc] = db + OFF_BAR + 8 * (B_X + 2 * dw);
        }
        if (UG) mbar_wait_lazy(bars + 8 * B_P1);
#pragma unroll 1
        for (int hf = 0; hf < 2; hf++) {
          mbar_wait_lazy(bars + 8 * (B_U + j) + 24 * hf);
#pragma unroll
          for (int hc = 0; hc < 2; hc++) {
            uint32_t r[4][4];
#pragma unroll
            for (int g = 0; g < 4; g++) ldsm4t(r[g], ((ro + OFF_RU) ^ (16 * hc)) + 12288 * hf + 256 * g);
#pragma unroll
            for (int g = 0; g < 4; g++) st_async4(da[hc] ^ (144 * g), bd[hc], r[g][0], r[g][1], r[g][2], r[g][3]);
            da[hc] += 4096; bd[hc] += 8;
          }
          TSTAMP(8 + hf);
        }
#pragma unroll
        for (int hc = 0; hc < 2; hc++) {
          const uint32_t pr = 4 * hc + (cl >> 1), sl = pr >= 2 ? pr + 1 : pr, dr = (sl * 11) >> 5, dw = sl - 3 * dr, db = mapa(sb, dr);
          da[hc] = db + OFF_XT + 24576 + 8192 * dw + xo; bd[hc] = db + OFF_BAR + 8 * (B_X + 6 + 2 * dw);
        }
        mbar_wait_lazy(bars + 8 * B_KG);
#pragma unroll 1
        for (int st = 0; st < 4; st++) {
          const int hf = st >> 1, hc = st & 1;
          const uint32_t w0 = hc ? sh[1][0] : sh[0][0], w1 = hc ? sh[1][1] : sh[0][1], dd = (hc ? da[1] : da[0]) + 4096 * hf, bb = (hc ? bd[1] : bd[0]) + 8 * hf;
          const uint32_t s0 = prmt(w0, 0, 0x1010), s1 = prmt(w0, 0, 0x3232), s2 = prmt(w1, 0, 0x1010), s3 = prmt(w1, 0, 0x3232);
          const uint32_t ho = (OFF_RK2 - OFF_RK1) * hf, a1 = (ro1 ^ (16 * hc)) + ho, a2 = (ro2 ^ (16 * hc)) + ho, av = (ro ^ (16 * hc)) + ho;
          if (!hc) mbar_wait_lazy(bars + 8 * (B_KV + j) + 24 * hf);
#pragma unroll
          for (int g2 = 0; g2 < 2; g2++) {
            uint32_t r[2][4], kk[2][4], hh[2][2];
#pragma unroll
            for (int s = 0; s < 2; s++) { const int o = 256 * (2 * g2 + s); ldsm4t(kk[s], a1 + OFF_RK1 + o); ldsm2t(hh[s], a2 + OFF_RK1 + o); ldsm4t(r[s], av + OFF_RV1 + o); }
#pragma unroll
            for (int s = 0; s < 2; s++) {
              const uint32_t om = prmt(hh[s][0], hh[s][1], 0x5432), o0 = prmt(hh[s][1], kk[s][0], 0x5432), o1 = prmt(kk[s][0], kk[s][1], 0x5432),
                             o2 = prmt(kk[s][1], kk[s][2], 0x5432), o3 = prmt(kk[s][2], kk[s][3], 0x5432);
              r[s][0] = hmul(hfma(kk[s][0], s0, hfma(o0, s1, hfma(hh[s][1], s2, hmul(om, s3)))), r[s][0]);
              r[s][1] = hmul(hfma(kk[s][1], s0, hfma(o1, s1, hfma(kk[s][0], s2, hmul(o0, s3)))), r[s][1]);
              r[s][2] = hmul(hfma(kk[s][2], s0, hfma(o2, s1, hfma(kk[s][1], s2, hmul(o1, s3)))), r[s][2]);
              r[s][3] = hmul(hfma(kk[s][3], s0, hfma(o3, s1, hfma(kk[s][2], s2, hmul(o2, s3)))), r[s][3]);
              st_async4(dd ^ (144 * (2 * g2 + s)), bb, r[s][0], r[s][1], r[s][2], r[s][3]);
            }
          }
          if (hc) TSTAMP(10 + hf);
        }
        const int i8 = lane & 7, hq = (lane >> 3) & 1, t0 = 8 * (lane >> 4), t = t0 + i8;
        const uint32_t yo = sb + 4096 * j + 256 * (8 * hq + i8) + ((2 * t0) ^ (i8 << 4)), oo = sb + 4096 * j + 32 * t + 16 * (hq ^ ((t >> 2) & 1));
#pragma unroll 1
        for (int fh = 0; fh < 2; fh++) {
          uint32_t y[8][4];
          mbar_wait_lazy(bars + 8 * (B_Y + j) + 24 * fh);
#pragma unroll
          for (int g = 0; g < 8; g++) ldsm4t(y[g], ((yo + OFF_YA) ^ (32 * (g & 3))) + 128 * (g >> 2) + 12288 * fh);
#pragma unroll
          for (int g = 0; g < 8; g++) stsm4(oo + OFF_RU + 512 * g + 12288 * fh, y[g][0], y[g][1], y[g][2], y[g][3]);
          fence_async();
          __syncwarp();
          if (lane == 0) tma5d_store(&p.mo, sb + OFF_RU + 4096 * j + 12288 * fh, ch0, 4 * (8 * fh + cg));
          TSTAMP(12 + fh);
        }
        {
          uint32_t q[8][4];
          mbar_wait_lazy(bars + 8 * (B_Q + j));
#pragma unroll
          for (int g = 0; g < 8; g++) ldsm4(q[g], oo + OFF_RQ + 512 * g);
          mbar_wait(bars + 8 * (B_Y + 6 + j));
#pragma unroll
          for (int g2 = 0; g2 < 2; g2++) {
            uint32_t y[4][4];
#pragma unroll
            for (int g = 0; g < 4; g++) ldsm4t(y[g], ((yo + OFF_XT) ^ (32 * g)) + 128 * g2);
#pragma unroll
            for (int g = 0; g < 4; g++) {
              const uint32_t* qq = q[4 * g2 + g];
              stsm4(oo + OFF_RQ + 512 * (4 * g2 + g), hmul(y[g][0], qq[0]), hmul(y[g][1], qq[1]), hmul(y[g][2], qq[2]), hmul(y[g][3], qq[3]));
            }
          }
          fence_async();
          __syncwarp();
          if (lane == 0) tma5d_store(&p.mo, sb + OFF_RQ + 4096 * j, DCH + ch0, 4 * cg);
          TSTAMP(14);
        }
        if (lane == 0) asm volatile("cp.async.bulk.wait_group.read 0;" ::: "memory");
      }
    }
    STAMP_FLUSH();
  } else {
    asm volatile("barrier.cluster.arrive.relaxed.aligned;" ::: "memory");
    const int slot = 3 * rank + wg;
    const bool hasA = slot < 8, hasB = slot != 2;
    const int pa = hasA ? slot : 0, pb = slot < 2 ? slot : slot - 1;
    if (wg == 0 && lane == 0) { asm volatile("prefetch.tensormap [%0];" ::"l"(&p.mk + warp) : "memory"); if (warp == 0) asm volatile("prefetch.tensormap [%0];" ::"l"(&p.mo) : "memory"); }
    const uint32_t so = (sb & 0x3FFFF) >> 4;
    const int ca = 2 * pa + (warp >> 1), cb = 2 * pb + (warp >> 1);
    const uint32_t yoa = OFF_YA + 256 * ca + ((8 * lane) ^ ((ca & 7) << 4));
    uint32_t ya[4], yb[4];
#pragma unroll
    for (int i = 0; i < 4; i++) {
      const uint32_t b = warp & 1, dr = i == 0 ? b : i == 3 ? b + 1 : 2 * b, sl = i == 0 ? b : i == 3 ? 2 * b : i - b, base = mapa(sb, dr);
      ya[i] = base + 4096 * sl + yoa + (hasA ? 0 : 12288);
      yb[i] = base + OFF_BAR + 8 * (B_Y + sl) + (hasA ? 0 : 24);
      asm volatile("" : "+r"(ya[i]), "+r"(yb[i]));
    }
    uint32_t sa = sb + OFF_KB + 8192 * wg + 1024 * (lane >> 3) + 256 * warp + 16 * (lane & 7);
    uint32_t la = sb + OFF_KB + 8192 * wg + 2048 * warp + 1024 * ((lane >> 3) & 1) + 128 * (lane >> 4) + 16 * (lane & 7);
    const uint4* ctp = g_ctab + t128;
    asm volatile("" : "+r"(sa), "+r"(la), "+l"(ctp));
    GenAddr ad;
    gen_addr(ad, sb, wg, warp, lane);
    asm volatile("setmaxnreg.inc.sync.aligned.u32 144;");
    STAMP(11);
    const int ord = rank == 2 ? (wg == 2 ? 0 : wg + 1) : wg;
    if (ord && slot != 5 && w_aim * zero == 0u) delay_clks(STAGGER * ord);
    STAMP(0);
    Consts k;
    if (slot != 5) {
      gen_kernels(ad, sb, wg, warp, lane, w_are, w_aim, w_bre, w_bim, w_cre, w_cim, w_ldt, k, ctp PROF_ARGS);
      fence_async();
    } else {
      asm volatile("barrier.cluster.wait.acquire.aligned; // idle" ::: "memory");
      load_consts(k, ctp);
    }
    STAMP(10);
    mbar_wait(bars + 8 * B_F);
    wg_bar(1 + wg);
    if (t128 < 3)
      asm volatile("mbarrier.arrive.relaxed.cluster.shared::cluster.b64 _, [%0];" ::"r"(mapa(bars + 8 * B_KG, t128)) : "memory");
    if (slot == 8 && t128 == 0)
      asm volatile("cp.async.bulk.shared::cluster.shared::cta.mbarrier::complete_tx::bytes [%0], [%1], 8192, [%2];" ::"r"(mapa(sb, 1) + OFF_KB + 16384), "r"(sb + OFF_KB + 16384), "r"(mapa(sb, 1) + OFF_BAR + 8 * B_KR) : "memory");
    STAMP(3);
#pragma unroll 1
    for (int ty = 0; ty < 2; ty++) {
      if (ty) {
        const uint32_t l8 = 8 * (threadIdx.x & 31);
        next_y(ya, yb, OFF_XT - OFF_YA - 12288 + 256 * (cb - ca) + (l8 ^ ((cb & 7) << 4)) - (l8 ^ ((ca & 7) << 4)));
        sa += 24576; la += 24576;
      }
      if (ty ? hasB : hasA) {
        const uint32_t kb = OFF_KB + 24576 * ty + 8192 * wg, dw = lds32(sb + OFF_D + 32 * ty + 4 * (ty ? pb : pa));
        if (ty) mbar_wait(bars + 8 * (B_S + wg));
        else if (slot == 5) { if (warp == 0) mbar_wait(bars + 8 * B_KR); wg_bar(1 + wg); }
        conv_pair(k, so + (kb >> 4), so + ((kb + OFF_XT) >> 4), so + (OFF_F2 >> 4), bars + 8 * (B_X + 6 * ty + 2 * wg), bars + 8 * (ty ? B_Y + 3 : B_KG),
                  prmt(dw, 0, 0x1010), prmt(dw, 0, 0x3232), ya, yb, sa, la, 1 + wg
);
        STAMP(8 + 8 * ty);
      }
    }
    if (wg < nchunk) {
      const int i8 = lane & 7, hq = (lane >> 3) & 1, t0 = 32 * warp + 8 * (lane >> 4), t = t0 + i8;
      const uint32_t yo = sb + OFF_XT + 4096 * (3 + wg) + 256 * (8 * hq + i8) + ((2 * t0) ^ (i8 << 4)), oo = sb + OFF_RQ + 4096 * (3 + wg) + 32 * t + 16 * (hq ^ ((t >> 2) & 1));
      uint32_t q[8], y[8];
      mbar_wait(bars + 8 * (B_Q + 3 + wg));
      ldsm4(q, oo); ldsm4(q + 4, oo + 512);
      if (warp == wg) mbar_wait(bars + 8 * (B_Y + 9 + wg));
      wg_bar(1 + wg);
      STAMP(18);
      ldsm4t(y, yo); ldsm4t(y + 4, yo ^ 32);
      stsm4(oo, hmul(y[0], q[0]), hmul(y[1], q[1]), hmul(y[2], q[2]), hmul(y[3], q[3]));
      stsm4(oo + 512, hmul(y[4], q[4]), hmul(y[5], q[5]), hmul(y[6], q[6]), hmul(y[7], q[7]));
      fence_async();
      wg_bar(1 + wg);
      if (t128 == 0) { tma5d_store(&p.mo, sb + OFF_RQ + 4096 * (3 + wg), DCH + ch0, 4 * (8 + cbase + wg)); asm volatile("cp.async.bulk.wait_group.read 0;" ::: "memory"); }
    }
    STAMP(20);
    STAMP_FLUSH();
  }
}

typedef CUresult (*EncodeFn)(CUtensorMap*, CUtensorMapDataType, cuuint32_t, void*, const cuuint64_t*, const cuuint64_t*, const cuuint32_t*, const cuuint32_t*,
                             CUtensorMapInterleave, CUtensorMapSwizzle, CUtensorMapL2promotion, CUtensorMapFloatOOBfill);

static void encode(EncodeFn fn, CUtensorMap* m, const void* base, int rank, const cuuint64_t* dims, const cuuint64_t* strides, const cuuint32_t* box, CUtensorMapSwizzle sw) {
  const cuuint32_t es[5] = {1, 1, 1, 1, 1};
  fn(m, CU_TENSOR_MAP_DATA_TYPE_BFLOAT16, rank, const_cast<void*>(base), dims, strides, box, es, CU_TENSOR_MAP_INTERLEAVE_NONE, sw,
     CU_TENSOR_MAP_L2_PROMOTION_NONE, CU_TENSOR_MAP_FLOAT_OOB_FILL_NONE);
}

}

constexpr int g_grid = 108;

extern "C" void kernel_launch(void* const* d_in, const int* in_sizes, int n_in, void* d_out, int out_size) {
  using namespace s4h3;
  (void)in_sizes; (void)n_in; (void)out_size;
  void* fnp = nullptr;
  cudaDriverEntryPointQueryResult qr;
  cudaGetDriverEntryPoint("cuTensorMapEncodeTiled", &fnp, cudaEnableDefault, &qr);
  EncodeFn fn = (EncodeFn)fnp;
  Maps p;
  {
    const cuuint64_t dims[4] = {DCH, 2, SEQ / 8, 4}, st[3] = {DCH * 2, DCH * 16, DCH * 4};
    const cuuint32_t b16[4] = {16, 2, 16, 4}, b17[4] = {16, 2, 17, 4};
    encode(fn, &p.mu, d_in[0], 4, dims, st, b16, CU_TENSOR_MAP_SWIZZLE_32B);
    encode(fn, &p.mk, d_in[10], 4, dims, st, b17, CU_TENSOR_MAP_SWIZZLE_32B);
    encode(fn, &p.mv, d_in[11], 4, dims, st, b16, CU_TENSOR_MAP_SWIZZLE_32B);
  }
  {
    const cuuint64_t dq[5] = {DCH, 2, 2, SEQ / 32, 8}, sq[4] = {DCH * 32, DCH * 16, DCH * 64, DCH * 2};
    const cuuint64_t dout[5] = {2 * DCH, 2, 2, SEQ / 32, 8}, so[4] = {DCH * 64, DCH * 32, DCH * 128, DCH * 4};
    const cuuint64_t ds[2] = {64, DCH * 32}, ss[1] = {128};
    const cuuint32_t bq[5] = {16, 2, 2, 4, 8}, bs[2] = {64, 64};
    encode(fn, &p.mq, d_in[9], 5, dq, sq, bq, CU_TENSOR_MAP_SWIZZLE_32B);
    encode(fn, &p.ms, d_in[13], 2, ds, ss, bs, CU_TENSOR_MAP_SWIZZLE_128B);
    encode(fn, &p.mo, d_out, 5, dout, so, bq, CU_TENSOR_MAP_SWIZZLE_32B);
  }
  void *ctab = nullptr, *f2tab = nullptr;
  cudaGetSymbolAddress(&ctab, CTAB);
  cudaGetSymbolAddress(&f2tab, F2TAB);
  auto rel = [&](int i) { return (int)(((const char*)d_in[i] - (const char*)d_in[1]) / 256); };
  cudaFuncSetAttribute(s4h3_kernel, cudaFuncAttributeMaxDynamicSharedMemorySize, SMEM_BYTES);
  s4h3_kernel<<<g_grid, NTHREADS, SMEM_BYTES, cudaStreamPerThread>>>(
      (const uint32_t*)d_in[1], rel(2), rel(3), rel(4), rel(5), rel(6), rel(7), 0u,
      (const uint4*)ctab, (const uint32_t*)d_in[8], (const uint32_t*)d_in[14], (const uint32_t*)d_in[12], (const uint32_t*)f2tab,
      p);
}
```
